```python
import torch

def _softmax(x, axis=-1):
    return torch.softmax(x, dim=axis)
def _gelu(x):
    return torch.nn.functional.gelu(x, approximate="tanh")
def _silu(x):
    return torch.nn.functional.silu(x)
def _sigmoid(x):
    return torch.sigmoid(x)
def _layernorm(x, axis=-1, eps=1e-5):
    m = x.mean(dim=axis, keepdim=True)
    v = x.var(dim=axis, keepdim=True, unbiased=False)
    return (x - m) / torch.sqrt(v + eps)
def _scatter_add(tgt, idx, src, axis=0):
    return tgt.clone().index_add_(axis, idx, src)
def _segment_sum(src, seg, n):
    out = torch.zeros((n,) + src.shape[1:], dtype=src.dtype)
    return out.index_add_(0, seg, src)
def _pad(x, pw):
    flat = tuple(v for pair in reversed(pw) for v in pair)
    return torch.nn.functional.pad(x, flat)

kernel_name = 'gated_mix__gqa_block_cached__glu_gated_reglu__decode'

def setup_inputs():

    _w = (lambda a: (lambda t: t.to(torch.bfloat16) if t.is_floating_point() else t)(torch.as_tensor(a)))
    def _A_setup():
        B, Sq, D = 4, 1, 512
        Hq, Hkv, Sk, Dh = 32, 8, 16384, 128
        assert Hq % Hkv == 0, (Hq, Hkv)
        return {
            "x": _w((lambda *s: torch.randn(*s, dtype=torch.bfloat16) * 0.05)(B, Sq, D)),
            "k_cache": _w((lambda *s: torch.randn(*s, dtype=torch.bfloat16) * 3.2)(B, Hkv, Sk, Dh)),
            "v_cache": _w((lambda *s: torch.randn(*s, dtype=torch.bfloat16) * 0.2)(B, Hkv, Sk, Dh)),
            "wq": _w((lambda *s: torch.randn(*s, dtype=torch.bfloat16) * 3.2)(D, Hq * Dh) * (D ** -0.5)),
            "wo": _w((lambda *s: torch.randn(*s, dtype=torch.bfloat16) * 0.2)(Hq * Dh, D) * ((Hq * Dh) ** -0.5)),
        }
    _A_in = _A_setup()

    def _B_setup():
        B, S, D, F = 4, 1, 512, 1792
        return {
            "x": _w((lambda *s: torch.randn(*s, dtype=torch.bfloat16) * 0.05)(B, S, D)),
            "W_gate": _w((lambda *s: torch.randn(*s, dtype=torch.bfloat16) * 0.4)(D, F) * (2.0 / D) ** 0.5),
            "W_up": _w((lambda *s: torch.randn(*s, dtype=torch.bfloat16) * 0.4)(D, F) * (2.0 / D) ** 0.5),
            "W_down": _w((lambda *s: torch.randn(*s, dtype=torch.bfloat16) * 0.4)(F, D) * (1.0 / F) ** 0.5),
        }
    _B_in = _B_setup()

    return {
        "A_x": _A_in["x"],
        "A_k_cache": _A_in["k_cache"],
        "A_v_cache": _A_in["v_cache"],
        "A_wq": _A_in["wq"],
        "A_wo": _A_in["wo"],
        "B_x": _B_in["x"],
        "B_W_gate": _B_in["W_gate"],
        "B_W_up": _B_in["W_up"],
        "B_W_down": _B_in["W_down"],
        "gate_w": _w((lambda *s: torch.randn(*s, dtype=torch.bfloat16) * 0.05)(512) * 16.0),
    }

def reference(A_x, A_k_cache, A_v_cache, A_wq, A_wo, B_x, B_W_gate, B_W_up, B_W_down, gate_w):
    def _A_ref(x, k_cache, v_cache, wq, wo):
        B, Sq, D = x.shape
        Hq, Dh = 32, 128
        Hkv = k_cache.shape[1]
        rep = Hq // Hkv
        q = (lambda x, *d: x.permute(*d))((x @ wq).reshape(B, Sq, Hq, Dh), 0, 2, 1, 3)
        k = (lambda x, n, axis: torch.repeat_interleave(x, n, dim=axis))(k_cache, rep, axis=1)
        v = (lambda x, n, axis: torch.repeat_interleave(x, n, dim=axis))(v_cache, rep, axis=1)
        scores = torch.einsum("bhqd,bhkd->bhqk", q, k) * (Dh ** -0.5)
        p = _softmax(scores, axis=-1)
        o = torch.einsum("bhqk,bhkd->bhqd", p, v)
        return (lambda x, *d: x.permute(*d))(o, 0, 2, 1, 3).reshape(B, Sq, Hq * Dh) @ wo

    def _B_ref(x, W_gate, W_up, W_down):
        gate = torch.einsum("bsd,df->bsf", x, W_gate)
        up = torch.einsum("bsd,df->bsf", x, W_up)
        gate = gate * (lambda x, dt: x.to(dt))(gate > 0, gate.dtype)
        h = gate * up
        return torch.einsum("bsf,fd->bsd", h, W_down)

    x = A_x
    g = _sigmoid((x * gate_w).sum(-1, keepdims=True))
    a = _A_ref(x, A_k_cache, A_v_cache, A_wq, A_wo)
    b = _B_ref(x, B_W_gate, B_W_up, B_W_down)
    return g * a + (1 - g) * b
```

```cpp
#include <cuda_runtime.h>
#include <cuda_bf16.h>
#include <cuda.h>
#include <stdint.h>

namespace {

constexpr int kB = 4, kD = 512, kHQ = 32, kHKV = 8, kDH = 128, kSK = 16384, kF = 1792;
constexpr int NATT = 128;
constexpr int NFFN = 4;
constexpr int NCTA = NATT + NFFN;
constexpr int NSTAGE = 6;
constexpr int STAGE = 32768;
constexpr int NCW = 8;
constexpr int NTHREADS = (NCW + 1) * 32;
constexpr int KEYS_PER_CTA = kSK / 4;
constexpr int NT = KEYS_PER_CTA / 128;
constexpr int ATT_STAGES = 2 + 2 * NT;
constexpr int FCOLS = kF / NFFN;
constexpr int FBLK = FCOLS / 64;
constexpr int FFN_STAGES = 4 * FBLK + 2 * FBLK;

constexpr int XP = 520;
constexpr int QP = 136;
constexpr int HP = FCOLS + 8;
constexpr int COMB_W = 544;
constexpr int OFF_RING = 0;
constexpr int OFF_COMB = NSTAGE * STAGE;
constexpr int OFF_X = OFF_COMB + NCW * COMB_W * 4;
constexpr int OFF_Q = OFF_X + kB * XP * 2;
constexpr int OFF_H = OFF_Q + kB * QP * 2;
constexpr int OFF_MX = OFF_H + kB * HP * 2;
constexpr int OFF_L = OFF_MX + NCW * 4 * 4;
constexpr int OFF_MISC = OFF_L + NCW * 4 * 4;
constexpr int OFF_BAR = OFF_MISC + 16;
constexpr int SMEM_USED = OFF_BAR + 2 * NSTAGE * 8;
constexpr int SMEM_BYTES = SMEM_USED + 1024;
static_assert(SMEM_BYTES <= 232448, "smem");
static_assert(OFF_X % 16 == 0 && OFF_Q % 16 == 0 && OFF_H % 16 == 0 && OFF_BAR % 8 == 0, "align");

constexpr float kScaleLog2 = 0.08838834764831845f * 1.4426950408889634f;

__device__ uint32_t g_epoch;
__device__ __align__(128) uint32_t g_q[kB * kHQ * kDH];
__device__ __align__(128) uint32_t g_pa[NATT * 4 * kDH];
__device__ __align__(128) uint32_t g_ml[NATT * 4 * 2];
__device__ __align__(128) uint32_t g_pb[(kHQ + NFFN) * kB * kD];

__device__ __forceinline__ uint32_t smem_u32(const void* p) { return (uint32_t)__cvta_generic_to_shared(p); }
__device__ __forceinline__ void mbar_init(uint32_t bar, uint32_t cnt) {
    asm volatile("mbarrier.init.shared::cta.b64 [%0], %1;" ::"r"(bar), "r"(cnt));
}
__device__ __forceinline__ void mbar_expect_tx(uint32_t bar, uint32_t bytes) {
    asm volatile("mbarrier.arrive.expect_tx.shared::cta.b64 _, [%0], %1;" ::"r"(bar), "r"(bytes) : "memory");
}
__device__ __forceinline__ void mbar_arrive(uint32_t bar) {
    asm volatile("mbarrier.arrive.shared::cta.b64 _, [%0];" ::"r"(bar) : "memory");
}
__device__ __forceinline__ bool mbar_try_wait(uint32_t bar, uint32_t parity) {
    uint32_t ok;
    asm volatile("{\n.reg .pred p;\nmbarrier.try_wait.parity.shared::cta.b64 p, [%1], %2;\nselp.u32 %0, 1, 0, p;\n}"
                 : "=r"(ok) : "r"(bar), "r"(parity) : "memory");
    return ok;
}
__device__ __forceinline__ void mbar_wait(uint32_t bar, uint32_t parity) {
    if (mbar_try_wait(bar, parity)) return;
    const long long t0 = clock64();
    while (!mbar_try_wait(bar, parity)) {
        if (clock64() - t0 > 4000000000LL) __trap();
    }
}
__device__ __forceinline__ void tma2d(uint32_t dst, const CUtensorMap* m, int c0, int c1, uint32_t bar) {
    asm volatile("cp.async.bulk.tensor.2d.shared::cluster.global.mbarrier::complete_tx::bytes [%0], [%1, {%3, %4}], [%2];"
                 ::"r"(dst), "l"(m), "r"(bar), "r"(c0), "r"(c1) : "memory");
}
__device__ __forceinline__ void prefetch_tmap(const CUtensorMap* m) {
    asm volatile("prefetch.tensormap [%0];" ::"l"(m) : "memory");
}
__device__ __forceinline__ void ldsm4(uint32_t addr, uint32_t& r0, uint32_t& r1, uint32_t& r2, uint32_t& r3) {
    asm volatile("ldmatrix.sync.aligned.m8n8.x4.shared.b16 {%0,%1,%2,%3}, [%4];"
                 : "=r"(r0), "=r"(r1), "=r"(r2), "=r"(r3) : "r"(addr) : "memory");
}
__device__ __forceinline__ void ldsm4t(uint32_t addr, uint32_t& r0, uint32_t& r1, uint32_t& r2, uint32_t& r3) {
    asm volatile("ldmatrix.sync.aligned.m8n8.x4.trans.shared.b16 {%0,%1,%2,%3}, [%4];"
                 : "=r"(r0), "=r"(r1), "=r"(r2), "=r"(r3) : "r"(addr) : "memory");
}
__device__ __forceinline__ void mma16816(float (&c)[4], uint32_t a0, uint32_t a1, uint32_t a2, uint32_t a3,
                                         uint32_t b0, uint32_t b1) {
    asm volatile("mma.sync.aligned.m16n8k16.row.col.f32.bf16.bf16.f32 {%0,%1,%2,%3}, {%4,%5,%6,%7}, {%8,%9}, {%0,%1,%2,%3};"
                 : "+f"(c[0]), "+f"(c[1]), "+f"(c[2]), "+f"(c[3])
                 : "r"(a0), "r"(a1), "r"(a2), "r"(a3), "r"(b0), "r"(b1));
}
__device__ __forceinline__ float ex2(float x) {
    float y;
    asm("ex2.approx.ftz.f32 %0, %1;" : "=f"(y) : "f"(x));
    return y;
}
__device__ __forceinline__ uint32_t pack_bf16(float lo, float hi) {
    uint32_t r;
    asm("cvt.rn.bf16x2.f32 %0, %1, %2;" : "=r"(r) : "f"(hi), "f"(lo));
    return r;
}
__device__ __forceinline__ float bf16_round(float v) { return __bfloat162float(__float2bfloat16_rn(v)); }
__device__ __forceinline__ void bar_consumers() { asm volatile("bar.sync 1, 256;" ::: "memory"); }

__device__ __forceinline__ uint32_t tagw(float v, uint32_t tag) { return (__float_as_uint(v) & ~1u) | tag; }
__device__ __forceinline__ void st_rlx(uint32_t* p, uint32_t v) {
    asm volatile("st.relaxed.gpu.global.u32 [%0], %1;" ::"l"(p), "r"(v) : "memory");
}
__device__ __forceinline__ void st_rlx2(uint32_t* p, uint32_t a, uint32_t b) {
    asm volatile("st.relaxed.gpu.global.v2.u32 [%0], {%1,%2};" ::"l"(p), "r"(a), "r"(b) : "memory");
}
__device__ __forceinline__ uint4 ld_rlx4(const uint32_t* p) {
    uint4 v;
    asm volatile("ld.relaxed.gpu.global.v4.u32 {%0,%1,%2,%3}, [%4];"
                 : "=r"(v.x), "=r"(v.y), "=r"(v.z), "=r"(v.w) : "l"(p) : "memory");
    return v;
}
__device__ __forceinline__ uint2 ld_rlx2(const uint32_t* p) {
    uint2 v;
    asm volatile("ld.relaxed.gpu.global.v2.u32 {%0,%1}, [%2];" : "=r"(v.x), "=r"(v.y) : "l"(p) : "memory");
    return v;
}
__device__ __forceinline__ bool tag_ok(uint4 v, uint32_t tag) {
    return (((v.x ^ tag) | (v.y ^ tag) | (v.z ^ tag) | (v.w ^ tag)) & 1u) == 0;
}
__device__ __forceinline__ uint4 poll4(const uint32_t* p, uint32_t tag) {
    uint4 v = ld_rlx4(p);
    int it = 0;
    while (!tag_ok(v, tag)) {
        if (++it > (1 << 21)) __trap();
        v = ld_rlx4(p);
    }
    return v;
}

struct Params {
    const __nv_bfloat16* x;
    const __nv_bfloat16* gate_w;
    __nv_bfloat16* out;
};

__global__ void __launch_bounds__(NTHREADS, 1)
fused_decode_kernel(const __grid_constant__ CUtensorMap tm_k, const __grid_constant__ CUtensorMap tm_v,
                    const __grid_constant__ CUtensorMap tm_wq, const __grid_constant__ CUtensorMap tm_wo,
                    const __grid_constant__ CUtensorMap tm_wg, const __grid_constant__ CUtensorMap tm_wu,
                    const __grid_constant__ CUtensorMap tm_wd, const Params prm) {
    extern __shared__ uint8_t smem_raw[];
    const uint32_t sraw = smem_u32(smem_raw);
    const uint32_t sb = (sraw + 1023u) & ~1023u;
    uint8_t* sp = smem_raw + (sb - sraw);
    const int tid = threadIdx.x, warp = tid >> 5, lane = tid & 31;
    const int c = blockIdx.x;
    const bool is_ffn = c >= NATT;
    const uint32_t bar_full = sb + OFF_BAR, bar_empty = bar_full + NSTAGE * 8;

    if (warp == NCW) {
        if (lane == 0) {
            for (int s = 0; s < NSTAGE; s++) {
                mbar_init(bar_full + s * 8, 1);
                mbar_init(bar_empty + s * 8, NCW);
            }
            asm volatile("fence.mbarrier_init.release.cluster;" ::: "memory");
            asm volatile("fence.proxy.async.shared::cta;" ::: "memory");
        }
        const int nst = is_ffn ? FFN_STAGES : ATT_STAGES;
        const int kv_line0 = (((c >> 2) & 3) * kHKV + (c >> 4)) * (kSK * 2) + (c & 3) * (KEYS_PER_CTA * 2);
        const int f0 = (c - NATT) * FCOLS;
        auto issue = [&](int i, int s) {
            const uint32_t bar = bar_full + s * 8, dst = sb + OFF_RING + s * STAGE;
            mbar_expect_tx(bar, STAGE);
            if (!is_ffn) {
                if (i == 0) {
                    tma2d(dst, &tm_wq, 32 * c, 0, bar);
                    tma2d(dst + STAGE / 2, &tm_wq, 32 * c, 256, bar);
                } else if (i <= 2 * NT) {
                    const int t = (i - 1) >> 1;
                    tma2d(dst, ((i - 1) & 1) ? &tm_v : &tm_k, 0, kv_line0 + t * 256, bar);
                } else {
                    tma2d(dst, &tm_wo, 128 * (c & 3), 128 * (c >> 2), bar);
                    tma2d(dst + STAGE / 2, &tm_wo, 128 * (c & 3) + 64, 128 * (c >> 2), bar);
                }
            } else {
                if (i < 4 * FBLK) {
                    tma2d(dst, (i & 2) ? &tm_wu : &tm_wg, f0 + 64 * (i >> 2), 256 * (i & 1), bar);
                } else {
                    const int ii = i - 4 * FBLK;
#pragma unroll
                    for (int blk = 0; blk < 4; blk++)
                        tma2d(dst + blk * 8192, &tm_wd, 256 * (ii & 1) + 64 * blk, f0 + 64 * (ii >> 1), bar);
                }
            }
        };
        if (lane == 0) {
            for (int s = 0; s < NSTAGE; s++) issue(s, s);
        }
        __syncthreads();
        if (lane == 0) {
            int s = 0;
            uint32_t ph = 0;
            for (int i = NSTAGE; i < nst; i++) {
                mbar_wait(bar_empty + s * 8, ph);
                issue(i, s);
                if (++s == NSTAGE) { s = 0; ph ^= 1; }
            }
        }
        return;
    }

    {
        const uint4 xv = __ldg(reinterpret_cast<const uint4*>(prm.x) + tid);
        *reinterpret_cast<uint4*>(sp + OFF_X + ((tid >> 6) * XP + (tid & 63) * 8) * 2) = xv;
    }
    float* misc_f = reinterpret_cast<float*>(sp + OFF_MISC);
    uint32_t* misc_u = reinterpret_cast<uint32_t*>(sp + OFF_MISC);
    if (tid == 0) {
        uint32_t e;
        asm volatile("ld.relaxed.gpu.global.u32 %0, [%1];" : "=r"(e) : "l"(&g_epoch) : "memory");
        misc_u[1] = e;
    }
    if (warp == NCW - 1 && !is_ffn) {
        const int bf = c >> 5;
        const uint4* xp = reinterpret_cast<const uint4*>(prm.x + bf * kD) + lane * 2;
        const uint4* gp = reinterpret_cast<const uint4*>(prm.gate_w) + lane * 2;
        float acc = 0.f;
#pragma unroll
        for (int u = 0; u < 2; u++) {
            const uint4 a = __ldg(xp + u), g = __ldg(gp + u);
            const uint32_t aw[4] = {a.x, a.y, a.z, a.w}, gw[4] = {g.x, g.y, g.z, g.w};
#pragma unroll
            for (int e = 0; e < 4; e++) {
                acc = fmaf(__uint_as_float(aw[e] << 16), __uint_as_float(gw[e] << 16), acc);
                acc = fmaf(__uint_as_float(aw[e] & 0xffff0000u), __uint_as_float(gw[e] & 0xffff0000u), acc);
            }
        }
#pragma unroll
        for (int o = 16; o > 0; o >>= 1) acc += __shfl_xor_sync(0xffffffffu, acc, o);
        if (lane == 0) misc_f[0] = 1.f / (1.f + __expf(-acc));
    }
    __syncthreads();
    const uint32_t epoch = misc_u[1];
    const uint32_t tag = (epoch + 1u) & 1u;

    const int r8 = lane & 7, mi = lane >> 3;
    const int rr = lane >> 2, jj = lane & 3;
    int st = 0;
    uint32_t ph = 0;
    auto advance = [&]() { if (++st == NSTAGE) { st = 0; ph ^= 1; } };
    auto release = [&]() {
        __syncwarp();
        if (lane == 0) mbar_arrive(bar_empty + st * 8);
        advance();
    };
    const uint32_t x_addr = sb + OFF_X + ((r8 & 3) * XP + mi * 8) * 2;

    if (is_ffn) {
        const int fi = c - NATT;
        for (int jb = 0; jb < FBLK; jb++) {
            float gu[2][2][4];
#pragma unroll
            for (int m = 0; m < 2; m++) {
#pragma unroll
                for (int e = 0; e < 4; e++) gu[m][0][e] = gu[m][1][e] = 0.f;
#pragma unroll
                for (int kh = 0; kh < 2; kh++) {
                    mbar_wait(bar_full + st * 8, ph);
                    const uint32_t wb = sb + OFF_RING + st * STAGE + lane * 128 + ((warp ^ r8) << 4);
#pragma unroll
                    for (int kk = 0; kk < 8; kk++) {
                        uint32_t b0, b1, b2, b3, a0, a1, a2, a3;
                        ldsm4t(wb + kk * 4096, b0, b1, b2, b3);
                        ldsm4(x_addr + (kh * 256 + kk * 32) * 2, a0, a1, a2, a3);
                        mma16816(gu[m][0], a0, 0u, a1, 0u, b0, b1);
                        mma16816(gu[m][1], a2, 0u, a3, 0u, b2, b3);
                    }
                    release();
                }
            }
            const float g0 = bf16_round(gu[0][0][0] + gu[0][1][0]), g1 = bf16_round(gu[0][0][1] + gu[0][1][1]);
            const float u0 = bf16_round(gu[1][0][0] + gu[1][1][0]), u1 = bf16_round(gu[1][0][1] + gu[1][1][1]);
            const float h0 = (g0 > 0.f ? g0 : 0.f) * u0, h1 = (g1 > 0.f ? g1 : 0.f) * u1;
            if (lane < 16)
                *reinterpret_cast<uint32_t*>(sp + OFF_H + (rr * HP + jb * 64 + warp * 8 + jj * 2) * 2) = pack_bf16(h0, h1);
        }
        bar_consumers();
        float acc[2][4][4];
#pragma unroll
        for (int ch = 0; ch < 2; ch++)
#pragma unroll
            for (int n = 0; n < 4; n++)
#pragma unroll
                for (int e = 0; e < 4; e++) acc[ch][n][e] = 0.f;
        const uint32_t h_addr = sb + OFF_H + ((r8 & 3) * HP + mi * 8) * 2;
        for (int jb = 0; jb < FBLK; jb++) {
            uint32_t a[8];
            ldsm4(h_addr + (jb * 64) * 2, a[0], a[1], a[2], a[3]);
            ldsm4(h_addr + (jb * 64 + 32) * 2, a[4], a[5], a[6], a[7]);
#pragma unroll
            for (int ch = 0; ch < 2; ch++) {
                mbar_wait(bar_full + st * 8, ph);
                const uint32_t wb = sb + OFF_RING + st * STAGE + (warp >> 1) * 8192 + (lane & 15) * 128;
#pragma unroll
                for (int ks = 0; ks < 4; ks++) {
#pragma unroll
                    for (int np = 0; np < 2; np++) {
                        uint32_t b0, b1, b2, b3;
                        const int chunk = (warp & 1) * 4 + np * 2 + (lane >> 4);
                        ldsm4t(wb + ks * 2048 + ((chunk ^ r8) << 4), b0, b1, b2, b3);
                        mma16816(acc[ch][np * 2], a[ks * 2], 0u, a[ks * 2 + 1], 0u, b0, b1);
                        mma16816(acc[ch][np * 2 + 1], a[ks * 2], 0u, a[ks * 2 + 1], 0u, b2, b3);
                    }
                }
                release();
            }
        }
        if (lane < 16) {
            uint32_t* dst = g_pb + ((kHQ + fi) * kB + rr) * kD + (warp >> 1) * 64 + (warp & 1) * 32 + jj * 2;
#pragma unroll
            for (int ch = 0; ch < 2; ch++)
#pragma unroll
                for (int n = 0; n < 4; n++)
                    st_rlx2(dst + ch * 256 + n * 8, tagw(acc[ch][n][0], tag), tagw(acc[ch][n][1], tag));
        }
        return;
    }

    float* comb = reinterpret_cast<float*>(sp + OFF_COMB);
    float* mx_s = reinterpret_cast<float*>(sp + OFF_MX);
    float* l_s = reinterpret_cast<float*>(sp + OFF_L);
    const int hkv = c >> 4, batch = (c >> 2) & 3;

    {
        float qc[4][4];
#pragma unroll
        for (int n = 0; n < 4; n++)
#pragma unroll
            for (int e = 0; e < 4; e++) qc[n][e] = 0.f;
        uint32_t a[8];
        ldsm4(x_addr + (warp * 64) * 2, a[0], a[1], a[2], a[3]);
        ldsm4(x_addr + (warp * 64 + 32) * 2, a[4], a[5], a[6], a[7]);
        mbar_wait(bar_full + st * 8, ph);
#pragma unroll
        for (int ks = 0; ks < 4; ks++) {
            const int row = warp * 64 + ks * 16 + (lane & 15);
#pragma unroll
            for (int np = 0; np < 2; np++) {
                uint32_t b0, b1, b2, b3;
                const int chunk = np * 2 + (lane >> 4);
                ldsm4t(sb + OFF_RING + st * STAGE + row * 64 + ((chunk ^ ((row >> 1) & 3)) << 4), b0, b1, b2, b3);
                mma16816(qc[np * 2], a[ks * 2], 0u, a[ks * 2 + 1], 0u, b0, b1);
                mma16816(qc[np * 2 + 1], a[ks * 2], 0u, a[ks * 2 + 1], 0u, b2, b3);
            }
        }
        release();
        if (lane < 16) {
#pragma unroll
            for (int n = 0; n < 4; n++)
                *reinterpret_cast<float2*>(comb + warp * 128 + rr * 32 + n * 8 + jj * 2) = make_float2(qc[n][0], qc[n][1]);
        }
        bar_consumers();
        if (tid < 128) {
            float s = 0.f;
#pragma unroll
            for (int w = 0; w < NCW; w++) s += comb[w * 128 + tid];
            st_rlx(g_q + (tid >> 5) * (kHQ * kDH) + 32 * c + (tid & 31), tagw(s, tag));
            const uint32_t* qsrc = g_q + batch * (kHQ * kDH) + hkv * 512 + tid * 4;
            uint4 v = ld_rlx4(qsrc);
            int it = 0;
            while (!tag_ok(v, tag)) {
                if (++it > (1 << 21)) __trap();
                __nanosleep(64);
                v = ld_rlx4(qsrc);
            }
            uint2 pk;
            pk.x = pack_bf16(__uint_as_float(v.x), __uint_as_float(v.y));
            pk.y = pack_bf16(__uint_as_float(v.z), __uint_as_float(v.w));
            *reinterpret_cast<uint2*>(sp + OFF_Q + ((tid >> 5) * QP + (tid & 31) * 4) * 2) = pk;
        }
        bar_consumers();
    }
    uint32_t qa[8];
    {
        const uint32_t qaddr = sb + OFF_Q + ((r8 & 3) * QP + (r8 >> 2) * 64 + mi * 8) * 2;
        ldsm4(qaddr, qa[0], qa[1], qa[2], qa[3]);
        ldsm4(qaddr + 64, qa[4], qa[5], qa[6], qa[7]);
    }

    float o[4][4];
#pragma unroll
    for (int m = 0; m < 4; m++)
#pragma unroll
        for (int e = 0; e < 4; e++) o[m][e] = 0.f;
    float m_run = -INFINITY, l_run = 0.f;
    const uint32_t k_off = (warp * 32 + r8) * 128 + ((mi ^ r8) << 4);
    const uint32_t v_off = (warp * 32 + (mi >> 1) * 8 + r8) * 128 + (((mi & 1) ^ r8) << 4);
    const uint32_t pmask = lane < 16 ? 0x0000ffffu : 0xffff0000u;
    float fsum[4] = {0.f, 0.f, 0.f, 0.f};
    const int bf = c >> 5, col_f = (c & 31) * 16 + (warp & 3) * 4;

    for (int t = 0; t < NT; t++) {
        float s[4][4];
        mbar_wait(bar_full + st * 8, ph);
        {
            const uint32_t kb = sb + OFF_RING + st * STAGE;
#pragma unroll
            for (int g = 0; g < 4; g++) {
#pragma unroll
                for (int e = 0; e < 4; e++) s[g][e] = 0.f;
                uint32_t b0, b1, b2, b3;
                ldsm4(kb + k_off + g * 1024, b0, b1, b2, b3);
                mma16816(s[g], qa[0], 0u, qa[1], 0u, b0, b1);
                mma16816(s[g], qa[2], 0u, qa[3], 0u, b2, b3);
                ldsm4(kb + (k_off ^ 64u) + g * 1024, b0, b1, b2, b3);
                mma16816(s[g], qa[4], 0u, qa[5], 0u, b0, b1);
                mma16816(s[g], qa[6], 0u, qa[7], 0u, b2, b3);
            }
        }
        release();
        float sc[4];
#pragma unroll
        for (int g = 0; g < 4; g++) {
            const float v = lane < 16 ? s[g][0] : s[g][1];
            sc[g] = v + __shfl_xor_sync(0xffffffffu, v, 16);
        }
        float mx = fmaxf(fmaxf(sc[0], sc[1]), fmaxf(sc[2], sc[3]));
        mx = fmaxf(mx, __shfl_xor_sync(0xffffffffu, mx, 1));
        mx = fmaxf(mx, __shfl_xor_sync(0xffffffffu, mx, 2));
        float m_new = fmaxf(m_run, mx);
        if (t == NT - 1) {
            if (lane < 16 && jj == 0) mx_s[warp * 4 + rr] = m_new;
            bar_consumers();
#pragma unroll
            for (int w = 0; w < NCW; w++) m_new = fmaxf(m_new, mx_s[w * 4 + (rr & 3)]);
        }
        if (__any_sync(0xffffffffu, m_new > m_run)) {
            const float alpha = ex2((m_run - m_new) * kScaleLog2);
            l_run *= alpha;
            const float a0 = __shfl_sync(0xffffffffu, alpha, ((2 * jj) & 3) * 4);
            const float a1 = __shfl_sync(0xffffffffu, alpha, ((2 * jj + 1) & 3) * 4);
#pragma unroll
            for (int m = 0; m < 4; m++) {
                o[m][0] *= a0; o[m][1] *= a1; o[m][2] *= a0; o[m][3] *= a1;
            }
            m_run = m_new;
        }
        const float mc = m_run * kScaleLog2;
        uint32_t pb[4];
#pragma unroll
        for (int g = 0; g < 4; g++) {
            const float p = ex2(fmaf(sc[g], kScaleLog2, -mc));
            l_run += p;
            pb[g] = pack_bf16(p, p) & pmask;
        }
        if (t == NT - 4 && warp < 4) {
            uint4 v = make_uint4(0, 0, 0, 0);
            if (lane < NFFN) v = poll4(g_pb + ((kHQ + lane) * kB + bf) * kD + col_f, tag);
            __syncwarp();
            fsum[0] = __uint_as_float(v.x); fsum[1] = __uint_as_float(v.y);
            fsum[2] = __uint_as_float(v.z); fsum[3] = __uint_as_float(v.w);
#pragma unroll
            for (int e = 0; e < 4; e++) {
                fsum[e] += __shfl_xor_sync(0xffffffffu, fsum[e], 1);
                fsum[e] += __shfl_xor_sync(0xffffffffu, fsum[e], 2);
            }
        }
        mbar_wait(bar_full + st * 8, ph);
        {
            const uint32_t vb = sb + OFF_RING + st * STAGE;
#pragma unroll
            for (int oc = 0; oc < 2; oc++) {
#pragma unroll
                for (int m = 0; m < 4; m++) {
                    uint32_t a0, a1, a2, a3;
                    ldsm4t(vb + ((v_off + oc * 2048) ^ (m * 32)), a0, a1, a2, a3);
                    mma16816(o[m], a0, a1, a2, a3, pb[oc * 2], pb[oc * 2 + 1]);
                }
            }
        }
        release();
    }

    l_run += __shfl_xor_sync(0xffffffffu, l_run, 1);
    l_run += __shfl_xor_sync(0xffffffffu, l_run, 2);
    if (lane < 16 && jj == 0) l_s[warp * 4 + rr] = l_run;
    {
        float* dst = comb + warp * COMB_W + (jj >> 1) * 272 + rr * 4 + (jj & 1) * 2;
#pragma unroll
        for (int m = 0; m < 4; m++) {
            *reinterpret_cast<float2*>(dst + m * 64) = make_float2(o[m][0], o[m][1]);
            *reinterpret_cast<float2*>(dst + m * 64 + 32) = make_float2(o[m][2], o[m][3]);
        }
    }
    bar_consumers();
    {
        const float* src = comb + (tid >> 7) * 272 + (tid & 127) * 2;
        float2 acc = *reinterpret_cast<const float2*>(src);
#pragma unroll
        for (int w = 1; w < NCW; w++) {
            const float2 v = *reinterpret_cast<const float2*>(src + w * COMB_W);
            acc.x += v.x; acc.y += v.y;
        }
        uint32_t* dst = g_pa + (c * 4 + (tid & 1) * 2) * kDH + (tid >> 1);
        st_rlx(dst, tagw(acc.x, tag));
        st_rlx(dst + kDH, tagw(acc.y, tag));
        if (tid < 4) {
            float l = 0.f, m = mx_s[tid];
#pragma unroll
            for (int w = 0; w < NCW; w++) { l += l_s[w * 4 + tid]; m = fmaxf(m, mx_s[w * 4 + tid]); }
            st_rlx2(g_ml + (c * 4 + tid) * 2, tagw(m, tag), tagw(l, tag));
        }
    }

    uint32_t wf[8][4];
    mbar_wait(bar_full + st * 8, ph);
    {
        const uint32_t wb = sb + OFF_RING + st * STAGE + (warp >> 2) * 16384 + ((mi >> 1) * 8 + r8) * 128 +
                            ((((warp & 3) * 2 + (mi & 1)) ^ r8) << 4);
#pragma unroll
        for (int ks = 0; ks < 8; ks++) ldsm4t(wb + ks * 2048, wf[ks][0], wf[ks][1], wf[ks][2], wf[ks][3]);
    }
    {
        const int src_cta = (c & ~15) | ((warp >> 1) << 2) | mi;
        const int hh = (c >> 2) & 3;
        const uint32_t* po = g_pa + (src_cta * 4 + hh) * kDH + (warp & 1) * 64 + r8 * 8;
        const uint32_t* pm = g_ml + (src_cta * 4 + hh) * 2;
        uint4 v0, v1;
        uint2 ml;
        int it = 0;
        while (true) {
            v0 = ld_rlx4(po);
            v1 = ld_rlx4(po + 4);
            ml = ld_rlx2(pm);
            if (tag_ok(v0, tag) && tag_ok(v1, tag) && (((ml.x ^ tag) | (ml.y ^ tag)) & 1u) == 0) break;
            if (++it > (1 << 21)) __trap();
        }
        __syncwarp();
        const float ms = __uint_as_float(ml.x);
        float M = fmaxf(ms, __shfl_xor_sync(0xffffffffu, ms, 8));
        M = fmaxf(M, __shfl_xor_sync(0xffffffffu, M, 16));
        const float wgt = ex2((ms - M) * kScaleLog2);
        float L = wgt * __uint_as_float(ml.y);
        L += __shfl_xor_sync(0xffffffffu, L, 8);
        L += __shfl_xor_sync(0xffffffffu, L, 16);
        float v[8] = {__uint_as_float(v0.x), __uint_as_float(v0.y), __uint_as_float(v0.z), __uint_as_float(v0.w),
                      __uint_as_float(v1.x), __uint_as_float(v1.y), __uint_as_float(v1.z), __uint_as_float(v1.w)};
        const float sc = wgt / L;
        float u[4];
        const bool up = (lane & 16) != 0;
#pragma unroll
        for (int e = 0; e < 4; e++) {
            const float keep = (up ? v[e + 4] : v[e]) * sc, send = (up ? v[e] : v[e + 4]) * sc;
            u[e] = keep + __shfl_xor_sync(0xffffffffu, send, 16);
        }
        const bool up2 = (lane & 8) != 0;
        float z[2];
#pragma unroll
        for (int e = 0; e < 2; e++) {
            const float keep = up2 ? u[e + 2] : u[e], send = up2 ? u[e] : u[e + 2];
            z[e] = keep + __shfl_xor_sync(0xffffffffu, send, 8);
        }
        const int dim = (warp & 1) * 64 + r8 * 8 + (up ? 4 : 0) + (up2 ? 2 : 0);
        *reinterpret_cast<uint32_t*>(sp + OFF_Q + ((warp >> 1) * QP + dim) * 2) = pack_bf16(z[0], z[1]);
    }
    bar_consumers();
    {
        const uint32_t oaddr = sb + OFF_Q + ((r8 & 3) * QP + mi * 8) * 2;
        float acc0[4] = {0.f, 0.f, 0.f, 0.f}, acc1[4] = {0.f, 0.f, 0.f, 0.f};
#pragma unroll
        for (int kp = 0; kp < 4; kp++) {
            uint32_t b0, b1, b2, b3;
            ldsm4(oaddr + kp * 64, b0, b1, b2, b3);
            mma16816(acc0, wf[kp * 2][0], wf[kp * 2][1], wf[kp * 2][2], wf[kp * 2][3], b0, b1);
            mma16816(acc1, wf[kp * 2 + 1][0], wf[kp * 2 + 1][1], wf[kp * 2 + 1][2], wf[kp * 2 + 1][3], b2, b3);
        }
        if (jj < 2) {
            uint32_t* dst = g_pb + ((c >> 2) * kB + jj * 2) * kD + (c & 3) * 128 + warp * 16 + rr;
            st_rlx(dst, tagw(acc0[0] + acc1[0], tag));
            st_rlx(dst + kD, tagw(acc0[1] + acc1[1], tag));
            st_rlx(dst + 8, tagw(acc0[2] + acc1[2], tag));
            st_rlx(dst + kD + 8, tagw(acc0[3] + acc1[3], tag));
        }
    }
    if (warp < 4) {
        const uint4 v = poll4(g_pb + (lane * kB + bf) * kD + col_f, tag);
        __syncwarp();
        float a[4] = {__uint_as_float(v.x), __uint_as_float(v.y), __uint_as_float(v.z), __uint_as_float(v.w)};
#pragma unroll
        for (int ofs = 16; ofs > 0; ofs >>= 1)
#pragma unroll
            for (int e = 0; e < 4; e++) a[e] += __shfl_xor_sync(0xffffffffu, a[e], ofs);
        if (lane == 0) {
            const float g = misc_f[0];
            uint2 pk;
            pk.x = pack_bf16(g * a[0] + (1.f - g) * fsum[0], g * a[1] + (1.f - g) * fsum[1]);
            pk.y = pack_bf16(g * a[2] + (1.f - g) * fsum[2], g * a[3] + (1.f - g) * fsum[3]);
            *reinterpret_cast<uint2*>(prm.out + bf * kD + col_f) = pk;
            if (c == 0 && warp == 0) {
                asm volatile("st.relaxed.gpu.global.u32 [%0], %1;" ::"l"(&g_epoch), "r"(epoch + 1u) : "memory");
            }
        }
    }
}

typedef CUresult (*EncodeFn)(CUtensorMap*, CUtensorMapDataType, cuuint32_t, void*, const cuuint64_t*, const cuuint64_t*,
                             const cuuint32_t*, const cuuint32_t*, CUtensorMapInterleave, CUtensorMapSwizzle,
                             CUtensorMapL2promotion, CUtensorMapFloatOOBfill);

void encode2d(EncodeFn enc, CUtensorMap* m, const void* base, uint64_t cols, uint64_t rows, uint64_t pitch_bytes,
              uint32_t box_cols, uint32_t box_rows, CUtensorMapSwizzle swz) {
    cuuint64_t gd[2] = {cols, rows};
    cuuint64_t gs[1] = {pitch_bytes};
    cuuint32_t bd[2] = {box_cols, box_rows};
    cuuint32_t es[2] = {1, 1};
    enc(m, CU_TENSOR_MAP_DATA_TYPE_BFLOAT16, 2, const_cast<void*>(base), gd, gs, bd, es, CU_TENSOR_MAP_INTERLEAVE_NONE,
        swz, CU_TENSOR_MAP_L2_PROMOTION_L2_128B, CU_TENSOR_MAP_FLOAT_OOB_FILL_NONE);
}

}

extern "C" void kernel_launch(void* const* d_in, const int* in_sizes, int n_in, void* d_out, int out_size) {
    (void)in_sizes; (void)n_in; (void)out_size;
    static EncodeFn enc = nullptr;
    if (!enc) {
        void* fn = nullptr;
        cudaDriverEntryPointQueryResult qr;
        cudaGetDriverEntryPoint("cuTensorMapEncodeTiled", &fn, cudaEnableDefault, &qr);
        enc = reinterpret_cast<EncodeFn>(fn);
        cudaFuncSetAttribute(fused_decode_kernel, cudaFuncAttributeMaxDynamicSharedMemorySize, SMEM_BYTES);
    }
    CUtensorMap tk, tv, twq, two, twg, twu, twd;
    encode2d(enc, &tk, d_in[1], 64, (uint64_t)kB * kHKV * kSK * 2, 128, 64, 256, CU_TENSOR_MAP_SWIZZLE_128B);
    encode2d(enc, &tv, d_in[2], 64, (uint64_t)kB * kHKV * kSK * 2, 128, 64, 256, CU_TENSOR_MAP_SWIZZLE_128B);
    encode2d(enc, &twq, d_in[3], kHQ * kDH, kD, kHQ * kDH * 2, 32, 256, CU_TENSOR_MAP_SWIZZLE_64B);
    encode2d(enc, &two, d_in[4], kD, kHQ * kDH, kD * 2, 64, 128, CU_TENSOR_MAP_SWIZZLE_128B);
    encode2d(enc, &twg, d_in[6], kF, kD, kF * 2, 64, 256, CU_TENSOR_MAP_SWIZZLE_128B);
    encode2d(enc, &twu, d_in[7], kF, kD, kF * 2, 64, 256, CU_TENSOR_MAP_SWIZZLE_128B);
    encode2d(enc, &twd, d_in[8], kD, kF, kD * 2, 64, 64, CU_TENSOR_MAP_SWIZZLE_128B);
    Params prm;
    prm.x = reinterpret_cast<const __nv_bfloat16*>(d_in[0]);
    prm.gate_w = reinterpret_cast<const __nv_bfloat16*>(d_in[9]);
    prm.out = reinterpret_cast<__nv_bfloat16*>(d_out);
    fused_decode_kernel<<<NCTA, NTHREADS, SMEM_BYTES>>>(tk, tv, twq, two, twg, twu, twd, prm);
}
```

```cpp
#include <cuda_runtime.h>
#include <cuda_bf16.h>
#include <cuda.h>
#include <stdint.h>

#define EVICT_FIRST 1
#define WIN 2
#define INIT_WRITES 1

namespace {

constexpr int kB = 4, kD = 512, kHQ = 32, kHKV = 8, kDH = 128, kSK = 16384, kF = 1792;
constexpr int NATT = 128;
constexpr int NFFN = 4;
constexpr int NCTA = NATT + NFFN;
constexpr int NSTAGE = 6;
constexpr int STAGE = 32768;
constexpr int NCW = 8;
constexpr int NTHREADS = (NCW + 1) * 32;
constexpr int KEYS_PER_CTA = kSK / 4;
constexpr int NT = KEYS_PER_CTA / 128;
constexpr int ATT_STAGES = 2 + 2 * NT;
constexpr int FCOLS = kF / NFFN;
constexpr int FBLK = FCOLS / 64;
constexpr int FFN_STAGES = 4 * FBLK + 2 * FBLK;

constexpr int XP = 520;
constexpr int QP = 136;
constexpr int HP = FCOLS + 8;
constexpr int COMB_W = 544;
constexpr int OFF_RING = 0;
constexpr int OFF_COMB = NSTAGE * STAGE;
constexpr int OFF_X = OFF_COMB + NCW * COMB_W * 4;
constexpr int OFF_Q = OFF_X + kB * XP * 2;
constexpr int OFF_H = OFF_Q + kB * QP * 2;
constexpr int OFF_MX = OFF_H + kB * HP * 2;
constexpr int OFF_L = OFF_MX + NCW * 4 * 4;
constexpr int OFF_MISC = OFF_L + NCW * 4 * 4;
constexpr int OFF_BAR = OFF_MISC + 16;
constexpr int SMEM_USED = OFF_BAR + 2 * NSTAGE * 8;
constexpr int SMEM_BYTES = SMEM_USED + 1024;
static_assert(SMEM_BYTES <= 232448, "smem");
static_assert(OFF_X % 16 == 0 && OFF_Q % 16 == 0 && OFF_H % 16 == 0 && OFF_BAR % 8 == 0, "align");

constexpr float kScaleLog2 = 0.08838834764831845f * 1.4426950408889634f;

__device__ uint32_t g_epoch;
__device__ __align__(128) uint32_t g_q[kB * kHQ * kDH];
__device__ __align__(128) uint32_t g_pa[NATT * 4 * kDH];
__device__ __align__(128) uint32_t g_ml[NATT * 4 * 2];
__device__ __align__(128) uint32_t g_pb[(kHQ + NFFN) * kB * kD];

#define TS(i)
#define TSP(i)

__device__ __forceinline__ uint32_t smem_u32(const void* p) { return (uint32_t)__cvta_generic_to_shared(p); }
__device__ __forceinline__ void mbar_init(uint32_t bar, uint32_t cnt) {
    asm volatile("mbarrier.init.shared::cta.b64 [%0], %1;" ::"r"(bar), "r"(cnt));
}
__device__ __forceinline__ void mbar_expect_tx(uint32_t bar, uint32_t bytes) {
    asm volatile("mbarrier.arrive.expect_tx.shared::cta.b64 _, [%0], %1;" ::"r"(bar), "r"(bytes) : "memory");
}
__device__ __forceinline__ void mbar_arrive(uint32_t bar) {
    asm volatile("mbarrier.arrive.shared::cta.b64 _, [%0];" ::"r"(bar) : "memory");
}
__device__ __forceinline__ bool mbar_try_wait(uint32_t bar, uint32_t parity) {
    uint32_t ok;
    asm volatile("{\n.reg .pred p;\nmbarrier.try_wait.parity.shared::cta.b64 p, [%1], %2;\nselp.u32 %0, 1, 0, p;\n}"
                 : "=r"(ok) : "r"(bar), "r"(parity) : "memory");
    return ok;
}
__device__ __forceinline__ void mbar_wait(uint32_t bar, uint32_t parity) {
    if (mbar_try_wait(bar, parity)) return;
    const long long t0 = clock64();
    while (!mbar_try_wait(bar, parity)) {
        if (clock64() - t0 > 4000000000LL) __trap();
    }
}
__device__ __forceinline__ void tma2d(uint32_t dst, const CUtensorMap* m, int c0, int c1, uint32_t bar) {
    asm volatile("cp.async.bulk.tensor.2d.shared::cluster.global.mbarrier::complete_tx::bytes [%0], [%1, {%3, %4}], [%2];"
                 ::"r"(dst), "l"(m), "r"(bar), "r"(c0), "r"(c1) : "memory");
}
__device__ __forceinline__ void tma2d_hint(uint32_t dst, const CUtensorMap* m, int c0, int c1, uint32_t bar, uint64_t pol) {
    asm volatile("cp.async.bulk.tensor.2d.shared::cluster.global.mbarrier::complete_tx::bytes.L2::cache_hint"
                 " [%0], [%1, {%3, %4}], [%2], %5;"
                 ::"r"(dst), "l"(m), "r"(bar), "r"(c0), "r"(c1), "l"(pol) : "memory");
}
__device__ __forceinline__ void prefetch_tmap(const CUtensorMap* m) {
    asm volatile("prefetch.tensormap [%0];" ::"l"(m) : "memory");
}
__device__ __forceinline__ void ldsm4(uint32_t addr, uint32_t& r0, uint32_t& r1, uint32_t& r2, uint32_t& r3) {
    asm volatile("ldmatrix.sync.aligned.m8n8.x4.shared.b16 {%0,%1,%2,%3}, [%4];"
                 : "=r"(r0), "=r"(r1), "=r"(r2), "=r"(r3) : "r"(addr) : "memory");
}
__device__ __forceinline__ void ldsm4t(uint32_t addr, uint32_t& r0, uint32_t& r1, uint32_t& r2, uint32_t& r3) {
    asm volatile("ldmatrix.sync.aligned.m8n8.x4.trans.shared.b16 {%0,%1,%2,%3}, [%4];"
                 : "=r"(r0), "=r"(r1), "=r"(r2), "=r"(r3) : "r"(addr) : "memory");
}
__device__ __forceinline__ void mma16816(float (&c)[4], uint32_t a0, uint32_t a1, uint32_t a2, uint32_t a3,
                                         uint32_t b0, uint32_t b1) {
    asm volatile("mma.sync.aligned.m16n8k16.row.col.f32.bf16.bf16.f32 {%0,%1,%2,%3}, {%4,%5,%6,%7}, {%8,%9}, {%0,%1,%2,%3};"
                 : "+f"(c[0]), "+f"(c[1]), "+f"(c[2]), "+f"(c[3])
                 : "r"(a0), "r"(a1), "r"(a2), "r"(a3), "r"(b0), "r"(b1));
}
__device__ __forceinline__ float ex2(float x) {
    float y;
    asm("ex2.approx.ftz.f32 %0, %1;" : "=f"(y) : "f"(x));
    return y;
}
__device__ __forceinline__ uint32_t pack_bf16(float lo, float hi) {
    uint32_t r;
    asm("cvt.rn.bf16x2.f32 %0, %1, %2;" : "=r"(r) : "f"(hi), "f"(lo));
    return r;
}
__device__ __forceinline__ float bf16_round(float v) { return __bfloat162float(__float2bfloat16_rn(v)); }
__device__ __forceinline__ void bar_consumers() { asm volatile("bar.sync 1, 256;" ::: "memory"); }

__device__ __forceinline__ uint32_t tagw(float v, uint32_t tag) { return (__float_as_uint(v) & ~1u) | tag; }
__device__ __forceinline__ void st_rlx(uint32_t* p, uint32_t v) {
    asm volatile("st.relaxed.gpu.global.u32 [%0], %1;" ::"l"(p), "r"(v) : "memory");
}
__device__ __forceinline__ void st_rlx2(uint32_t* p, uint32_t a, uint32_t b) {
    asm volatile("st.relaxed.gpu.global.v2.u32 [%0], {%1,%2};" ::"l"(p), "r"(a), "r"(b) : "memory");
}
__device__ __forceinline__ uint4 ld_rlx4(const uint32_t* p) {
    uint4 v;
    asm volatile("ld.relaxed.gpu.global.v4.u32 {%0,%1,%2,%3}, [%4];"
                 : "=r"(v.x), "=r"(v.y), "=r"(v.z), "=r"(v.w) : "l"(p) : "memory");
    return v;
}
__device__ __forceinline__ uint2 ld_rlx2(const uint32_t* p) {
    uint2 v;
    asm volatile("ld.relaxed.gpu.global.v2.u32 {%0,%1}, [%2];" : "=r"(v.x), "=r"(v.y) : "l"(p) : "memory");
    return v;
}
__device__ __forceinline__ bool tag_ok(uint4 v, uint32_t tag) {
    return (((v.x ^ tag) | (v.y ^ tag) | (v.z ^ tag) | (v.w ^ tag)) & 1u) == 0;
}
__device__ __forceinline__ uint4 poll4(const uint32_t* p, uint32_t tag) {
    uint4 v = ld_rlx4(p);
    int it = 0;
    while (!tag_ok(v, tag)) {
        if (++it > (1 << 21)) __trap();
        v = ld_rlx4(p);
    }
    return v;
}

struct Params {
    const __nv_bfloat16* x;
    const __nv_bfloat16* gate_w;
    __nv_bfloat16* out;
};

__global__ void __launch_bounds__(NTHREADS, 1)
fused_decode_kernel(const __grid_constant__ CUtensorMap tm_k, const __grid_constant__ CUtensorMap tm_v,
                    const __grid_constant__ CUtensorMap tm_wq, const __grid_constant__ CUtensorMap tm_wo,
                    const __grid_constant__ CUtensorMap tm_wg, const __grid_constant__ CUtensorMap tm_wu,
                    const __grid_constant__ CUtensorMap tm_wd, const Params prm) {
    extern __shared__ uint8_t smem_raw[];
    const uint32_t sraw = smem_u32(smem_raw);
    const uint32_t sb = (sraw + 1023u) & ~1023u;
    uint8_t* sp = smem_raw + (sb - sraw);
    const int tid = threadIdx.x, warp = tid >> 5, lane = tid & 31;
    const int c = blockIdx.x;
    const bool is_ffn = c >= NATT;
    const uint32_t bar_full = sb + OFF_BAR, bar_empty = bar_full + NSTAGE * 8;

    TS(0);
    if (warp == NCW) {
        if (lane == 0) {
            for (int s = 0; s < NSTAGE; s++) {
                mbar_init(bar_full + s * 8, 1);
                mbar_init(bar_empty + s * 8, NCW);
            }
            asm volatile("fence.mbarrier_init.release.cluster;" ::: "memory");
            asm volatile("fence.proxy.async.shared::cta;" ::: "memory");
        }
        const int nst = is_ffn ? FFN_STAGES : ATT_STAGES;
        const int kv_line0 = (((c >> 2) & 3) * kHKV + (c >> 4)) * (kSK * 2) + (c & 3) * (KEYS_PER_CTA * 2);
        const int f0 = (c - NATT) * FCOLS;
        uint64_t pol;
        asm volatile("createpolicy.fractional.L2::evict_first.b64 %0, 1.0;" : "=l"(pol));
        auto issue = [&](int i, int s) {
            const uint32_t bar = bar_full + s * 8, dst = sb + OFF_RING + s * STAGE;
            mbar_expect_tx(bar, STAGE);
            if (!is_ffn) {
                if (i == 0) {
                    tma2d(dst, &tm_wq, 32 * c, 0, bar);
                    tma2d(dst + STAGE / 2, &tm_wq, 32 * c, 256, bar);
                } else if (i <= 2 * NT) {
                    const int t = (i - 1) >> 1;
                    tma2d_hint(dst, ((i - 1) & 1) ? &tm_v : &tm_k, 0, kv_line0 + t * 256, bar, pol);
                } else {
                    tma2d(dst, &tm_wo, 128 * (c & 3), 128 * (c >> 2), bar);
                    tma2d(dst + STAGE / 2, &tm_wo, 128 * (c & 3) + 64, 128 * (c >> 2), bar);
                }
            } else {
                if (i < 4 * FBLK) {
                    tma2d(dst, (i & 2) ? &tm_wu : &tm_wg, f0 + 64 * (i >> 2), 256 * (i & 1), bar);
                } else {
                    const int ii = i - 4 * FBLK;
#pragma unroll
                    for (int blk = 0; blk < 4; blk++)
                        tma2d(dst + blk * 8192, &tm_wd, 256 * (ii & 1) + 64 * blk, f0 + 64 * (ii >> 1), bar);
                }
            }
        };
        if (lane == 0) {
            TSP(16);
            for (int s = 0; s < WIN; s++) issue(s, s);
            TSP(17);
        }
        __syncthreads();
        if (lane == 0) {
            int s = WIN % NSTAGE, sw = 0;
            uint32_t ph = WIN == NSTAGE ? 0 : 1, phw = 0;
            for (int i = WIN; i < nst; i++) {
                mbar_wait(bar_full + sw * 8, phw);
                if (i >= NSTAGE) mbar_wait(bar_empty + s * 8, ph);
                issue(i, s);
                if (++s == NSTAGE) { s = 0; ph ^= 1; }
                if (++sw == NSTAGE) { sw = 0; phw ^= 1; }
            }
            TSP(18);
        }
        return;
    }

    {
        const uint4 xv = __ldg(reinterpret_cast<const uint4*>(prm.x) + tid);
        *reinterpret_cast<uint4*>(sp + OFF_X + ((tid >> 6) * XP + (tid & 63) * 8) * 2) = xv;
    }
    float* misc_f = reinterpret_cast<float*>(sp + OFF_MISC);
    uint32_t* misc_u = reinterpret_cast<uint32_t*>(sp + OFF_MISC);
    if (tid == 0) {
        uint32_t e;
        asm volatile("ld.relaxed.gpu.global.u32 %0, [%1];" : "=r"(e) : "l"(&g_epoch) : "memory");
        misc_u[1] = e;
    }
    if (warp == NCW - 1 && !is_ffn) {
        const int bf = c >> 5;
        const uint4* xp = reinterpret_cast<const uint4*>(prm.x + bf * kD) + lane * 2;
        const uint4* gp = reinterpret_cast<const uint4*>(prm.gate_w) + lane * 2;
        float acc = 0.f;
#pragma unroll
        for (int u = 0; u < 2; u++) {
            const uint4 a = __ldg(xp + u), g = __ldg(gp + u);
            const uint32_t aw[4] = {a.x, a.y, a.z, a.w}, gw[4] = {g.x, g.y, g.z, g.w};
#pragma unroll
            for (int e = 0; e < 4; e++) {
                acc = fmaf(__uint_as_float(aw[e] << 16), __uint_as_float(gw[e] << 16), acc);
                acc = fmaf(__uint_as_float(aw[e] & 0xffff0000u), __uint_as_float(gw[e] & 0xffff0000u), acc);
            }
        }
#pragma unroll
        for (int o = 16; o > 0; o >>= 1) acc += __shfl_xor_sync(0xffffffffu, acc, o);
        if (lane == 0) misc_f[0] = 1.f / (1.f + __expf(-acc));
    }
    __syncthreads();
    TS(1);
    const uint32_t epoch = misc_u[1];
    const uint32_t tag = (epoch + 1u) & 1u;

    const int r8 = lane & 7, mi = lane >> 3;
    const int rr = lane >> 2, jj = lane & 3;
    int st = 0;
    uint32_t ph = 0;
    auto advance = [&]() { if (++st == NSTAGE) { st = 0; ph ^= 1; } };
    auto release = [&]() {
        __syncwarp();
        if (lane == 0) mbar_arrive(bar_empty + st * 8);
        advance();
    };
    const uint32_t x_addr = sb + OFF_X + ((r8 & 3) * XP + mi * 8) * 2;

    if (is_ffn) {
        const int fi = c - NATT;
        if (lane < 16) {
            uint32_t* dst = g_pb + ((kHQ + fi) * kB + rr) * kD + (warp >> 1) * 64 + (warp & 1) * 32 + jj * 2;
#pragma unroll
            for (int ch = 0; ch < 2; ch++)
#pragma unroll
                for (int n = 0; n < 4; n++) st_rlx2(dst + ch * 256 + n * 8, tag ^ 1u, tag ^ 1u);
        }
        for (int jb = 0; jb < FBLK; jb++) {
            float gu[2][2][4];
#pragma unroll
            for (int m = 0; m < 2; m++) {
#pragma unroll
                for (int e = 0; e < 4; e++) gu[m][0][e] = gu[m][1][e] = 0.f;
#pragma unroll
                for (int kh = 0; kh < 2; kh++) {
                    mbar_wait(bar_full + st * 8, ph);
                    const uint32_t wb = sb + OFF_RING + st * STAGE + lane * 128 + ((warp ^ r8) << 4);
#pragma unroll
                    for (int kk = 0; kk < 8; kk++) {
                        uint32_t b0, b1, b2, b3, a0, a1, a2, a3;
                        ldsm4t(wb + kk * 4096, b0, b1, b2, b3);
                        ldsm4(x_addr + (kh * 256 + kk * 32) * 2, a0, a1, a2, a3);
                        mma16816(gu[m][0], a0, 0u, a1, 0u, b0, b1);
                        mma16816(gu[m][1], a2, 0u, a3, 0u, b2, b3);
                    }
                    release();
                }
            }
            const float g0 = bf16_round(gu[0][0][0] + gu[0][1][0]), g1 = bf16_round(gu[0][0][1] + gu[0][1][1]);
            const float u0 = bf16_round(gu[1][0][0] + gu[1][1][0]), u1 = bf16_round(gu[1][0][1] + gu[1][1][1]);
            const float h0 = (g0 > 0.f ? g0 : 0.f) * u0, h1 = (g1 > 0.f ? g1 : 0.f) * u1;
            if (lane < 16)
                *reinterpret_cast<uint32_t*>(sp + OFF_H + (rr * HP + jb * 64 + warp * 8 + jj * 2) * 2) = pack_bf16(h0, h1);
        }
        bar_consumers();
        TS(10);
        float acc[2][4][4];
#pragma unroll
        for (int ch = 0; ch < 2; ch++)
#pragma unroll
            for (int n = 0; n < 4; n++)
#pragma unroll
                for (int e = 0; e < 4; e++) acc[ch][n][e] = 0.f;
        const uint32_t h_addr = sb + OFF_H + ((r8 & 3) * HP + mi * 8) * 2;
        for (int jb = 0; jb < FBLK; jb++) {
            uint32_t a[8];
            ldsm4(h_addr + (jb * 64) * 2, a[0], a[1], a[2], a[3]);
            ldsm4(h_addr + (jb * 64 + 32) * 2, a[4], a[5], a[6], a[7]);
#pragma unroll
            for (int ch = 0; ch < 2; ch++) {
                mbar_wait(bar_full + st * 8, ph);
                const uint32_t wb = sb + OFF_RING + st * STAGE + (warp >> 1) * 8192 + (lane & 15) * 128;
#pragma unroll
                for (int ks = 0; ks < 4; ks++) {
#pragma unroll
                    for (int np = 0; np < 2; np++) {
                        uint32_t b0, b1, b2, b3;
                        const int chunk = (warp & 1) * 4 + np * 2 + (lane >> 4);
                        ldsm4t(wb + ks * 2048 + ((chunk ^ r8) << 4), b0, b1, b2, b3);
                        mma16816(acc[ch][np * 2], a[ks * 2], 0u, a[ks * 2 + 1], 0u, b0, b1);
                        mma16816(acc[ch][np * 2 + 1], a[ks * 2], 0u, a[ks * 2 + 1], 0u, b2, b3);
                    }
                }
                release();
            }
        }
        if (lane < 16) {
            uint32_t* dst = g_pb + ((kHQ + fi) * kB + rr) * kD + (warp >> 1) * 64 + (warp & 1) * 32 + jj * 2;
#pragma unroll
            for (int ch = 0; ch < 2; ch++)
#pragma unroll
                for (int n = 0; n < 4; n++)
                    st_rlx2(dst + ch * 256 + n * 8, tagw(acc[ch][n][0], tag), tagw(acc[ch][n][1], tag));
        }
        TS(15);
        return;
    }

    float* comb = reinterpret_cast<float*>(sp + OFF_COMB);
    float* mx_s = reinterpret_cast<float*>(sp + OFF_MX);
    float* l_s = reinterpret_cast<float*>(sp + OFF_L);
    const int hkv = c >> 4, batch = (c >> 2) & 3;
    {
        const uint32_t nr = tag ^ 1u;
        if (tid < 128) st_rlx(g_q + (tid >> 5) * (kHQ * kDH) + 32 * c + (tid & 31), nr);
        uint32_t* dst = g_pa + (c * 4 + (tid & 1) * 2) * kDH + (tid >> 1);
        st_rlx(dst, nr);
        st_rlx(dst + kDH, nr);
        if (tid < 4) st_rlx2(g_ml + (c * 4 + tid) * 2, nr, nr);
        if (jj < 2) {
            uint32_t* d2 = g_pb + ((c >> 2) * kB + jj * 2) * kD + (c & 3) * 128 + warp * 16 + rr;
            st_rlx(d2, nr);
            st_rlx(d2 + kD, nr);
            st_rlx(d2 + 8, nr);
            st_rlx(d2 + kD + 8, nr);
        }
    }

    {
        float qc[4][4];
#pragma unroll
        for (int n = 0; n < 4; n++)
#pragma unroll
            for (int e = 0; e < 4; e++) qc[n][e] = 0.f;
        uint32_t a[8];
        ldsm4(x_addr + (warp * 64) * 2, a[0], a[1], a[2], a[3]);
        ldsm4(x_addr + (warp * 64 + 32) * 2, a[4], a[5], a[6], a[7]);
        mbar_wait(bar_full + st * 8, ph);
        TS(2);
#pragma unroll
        for (int ks = 0; ks < 4; ks++) {
            const int row = warp * 64 + ks * 16 + (lane & 15);
#pragma unroll
            for (int np = 0; np < 2; np++) {
                uint32_t b0, b1, b2, b3;
                const int chunk = np * 2 + (lane >> 4);
                ldsm4t(sb + OFF_RING + st * STAGE + row * 64 + ((chunk ^ ((row >> 1) & 3)) << 4), b0, b1, b2, b3);
                mma16816(qc[np * 2], a[ks * 2], 0u, a[ks * 2 + 1], 0u, b0, b1);
                mma16816(qc[np * 2 + 1], a[ks * 2], 0u, a[ks * 2 + 1], 0u, b2, b3);
            }
        }
        release();
        if (lane < 16) {
#pragma unroll
            for (int n = 0; n < 4; n++)
                *reinterpret_cast<float2*>(comb + warp * 128 + rr * 32 + n * 8 + jj * 2) = make_float2(qc[n][0], qc[n][1]);
        }
        bar_consumers();
        if (tid < 128) {
            float s = 0.f;
#pragma unroll
            for (int w = 0; w < NCW; w++) s += comb[w * 128 + tid];
            st_rlx(g_q + (tid >> 5) * (kHQ * kDH) + 32 * c + (tid & 31), tagw(s, tag));
            TS(3);
            const uint32_t* qsrc = g_q + batch * (kHQ * kDH) + hkv * 512 + tid * 4;
            uint4 v = ld_rlx4(qsrc);
            int it = 0;
            while (!tag_ok(v, tag)) {
                if (++it > (1 << 21)) __trap();
                __nanosleep(64);
                v = ld_rlx4(qsrc);
            }
            uint2 pk;
            pk.x = pack_bf16(__uint_as_float(v.x), __uint_as_float(v.y));
            pk.y = pack_bf16(__uint_as_float(v.z), __uint_as_float(v.w));
            *reinterpret_cast<uint2*>(sp + OFF_Q + ((tid >> 5) * QP + (tid & 31) * 4) * 2) = pk;
        }
        bar_consumers();
    }
    TS(4);
    uint32_t qa[8];
    {
        const uint32_t qaddr = sb + OFF_Q + ((r8 & 3) * QP + (r8 >> 2) * 64 + mi * 8) * 2;
        ldsm4(qaddr, qa[0], qa[1], qa[2], qa[3]);
        ldsm4(qaddr + 64, qa[4], qa[5], qa[6], qa[7]);
    }

    float o[4][4];
#pragma unroll
    for (int m = 0; m < 4; m++)
#pragma unroll
        for (int e = 0; e < 4; e++) o[m][e] = 0.f;
    float m_run = -INFINITY, l_run = 0.f;
    const uint32_t k_off = (warp * 32 + r8) * 128 + ((mi ^ r8) << 4);
    const uint32_t v_off = (warp * 32 + (mi >> 1) * 8 + r8) * 128 + (((mi & 1) ^ r8) << 4);
    const uint32_t pmask = lane < 16 ? 0x0000ffffu : 0xffff0000u;
    float fsum[4] = {0.f, 0.f, 0.f, 0.f};
    const int bf = c >> 5, col_f = (c & 31) * 16 + (warp & 3) * 4;

    for (int t = 0; t < NT; t++) {
        float s[4][4];
        mbar_wait(bar_full + st * 8, ph);
        {
            const uint32_t kb = sb + OFF_RING + st * STAGE;
#pragma unroll
            for (int g = 0; g < 4; g++) {
#pragma unroll
                for (int e = 0; e < 4; e++) s[g][e] = 0.f;
                uint32_t b0, b1, b2, b3;
                ldsm4(kb + k_off + g * 1024, b0, b1, b2, b3);
                mma16816(s[g], qa[0], 0u, qa[1], 0u, b0, b1);
                mma16816(s[g], qa[2], 0u, qa[3], 0u, b2, b3);
                ldsm4(kb + (k_off ^ 64u) + g * 1024, b0, b1, b2, b3);
                mma16816(s[g], qa[4], 0u, qa[5], 0u, b0, b1);
                mma16816(s[g], qa[6], 0u, qa[7], 0u, b2, b3);
            }
        }
        release();
        float sc[4];
#pragma unroll
        for (int g = 0; g < 4; g++) {
            const float v = lane < 16 ? s[g][0] : s[g][1];
            sc[g] = v + __shfl_xor_sync(0xffffffffu, v, 16);
        }
        float mx = fmaxf(fmaxf(sc[0], sc[1]), fmaxf(sc[2], sc[3]));
        mx = fmaxf(mx, __shfl_xor_sync(0xffffffffu, mx, 1));
        mx = fmaxf(mx, __shfl_xor_sync(0xffffffffu, mx, 2));
        float m_new = fmaxf(m_run, mx);
        if (t == NT - 1) {
            if (lane < 16 && jj == 0) mx_s[warp * 4 + rr] = m_new;
            bar_consumers();
#pragma unroll
            for (int w = 0; w < NCW; w++) m_new = fmaxf(m_new, mx_s[w * 4 + (rr & 3)]);
        }
        if (__any_sync(0xffffffffu, m_new > m_run)) {
            const float alpha = ex2((m_run - m_new) * kScaleLog2);
            l_run *= alpha;
            const float a0 = __shfl_sync(0xffffffffu, alpha, ((2 * jj) & 3) * 4);
            const float a1 = __shfl_sync(0xffffffffu, alpha, ((2 * jj + 1) & 3) * 4);
#pragma unroll
            for (int m = 0; m < 4; m++) {
                o[m][0] *= a0; o[m][1] *= a1; o[m][2] *= a0; o[m][3] *= a1;
            }
            m_run = m_new;
        }
        const float mc = m_run * kScaleLog2;
        uint32_t pb[4];
#pragma unroll
        for (int g = 0; g < 4; g++) {
            const float p = ex2(fmaf(sc[g], kScaleLog2, -mc));
            l_run += p;
            pb[g] = pack_bf16(p, p) & pmask;
        }
        if (t == NT - 4 && warp < 4) {
            uint4 v = make_uint4(0, 0, 0, 0);
            if (lane < NFFN) v = poll4(g_pb + ((kHQ + lane) * kB + bf) * kD + col_f, tag);
            __syncwarp();
            fsum[0] = __uint_as_float(v.x); fsum[1] = __uint_as_float(v.y);
            fsum[2] = __uint_as_float(v.z); fsum[3] = __uint_as_float(v.w);
#pragma unroll
            for (int e = 0; e < 4; e++) {
                fsum[e] += __shfl_xor_sync(0xffffffffu, fsum[e], 1);
                fsum[e] += __shfl_xor_sync(0xffffffffu, fsum[e], 2);
            }
        }
        mbar_wait(bar_full + st * 8, ph);
        {
            const uint32_t vb = sb + OFF_RING + st * STAGE;
#pragma unroll
            for (int oc = 0; oc < 2; oc++) {
#pragma unroll
                for (int m = 0; m < 4; m++) {
                    uint32_t a0, a1, a2, a3;
                    ldsm4t(vb + ((v_off + oc * 2048) ^ (m * 32)), a0, a1, a2, a3);
                    mma16816(o[m], a0, a1, a2, a3, pb[oc * 2], pb[oc * 2 + 1]);
                }
            }
        }
        release();
    }

    TS(10);
    l_run += __shfl_xor_sync(0xffffffffu, l_run, 1);
    l_run += __shfl_xor_sync(0xffffffffu, l_run, 2);
    if (lane < 16 && jj == 0) l_s[warp * 4 + rr] = l_run;
    {
        float* dst = comb + warp * COMB_W + (jj >> 1) * 272 + rr * 4 + (jj & 1) * 2;
#pragma unroll
        for (int m = 0; m < 4; m++) {
            *reinterpret_cast<float2*>(dst + m * 64) = make_float2(o[m][0], o[m][1]);
            *reinterpret_cast<float2*>(dst + m * 64 + 32) = make_float2(o[m][2], o[m][3]);
        }
    }
    bar_consumers();
    {
        const float* src = comb + (tid >> 7) * 272 + (tid & 127) * 2;
        float2 acc = *reinterpret_cast<const float2*>(src);
#pragma unroll
        for (int w = 1; w < NCW; w++) {
            const float2 v = *reinterpret_cast<const float2*>(src + w * COMB_W);
            acc.x += v.x; acc.y += v.y;
        }
        uint32_t* dst = g_pa + (c * 4 + (tid & 1) * 2) * kDH + (tid >> 1);
        st_rlx(dst, tagw(acc.x, tag));
        st_rlx(dst + kDH, tagw(acc.y, tag));
        if (tid < 4) {
            float l = 0.f, m = mx_s[tid];
#pragma unroll
            for (int w = 0; w < NCW; w++) { l += l_s[w * 4 + tid]; m = fmaxf(m, mx_s[w * 4 + tid]); }
            st_rlx2(g_ml + (c * 4 + tid) * 2, tagw(m, tag), tagw(l, tag));
        }
    }

    TS(11);
    uint32_t wf[8][4];
    mbar_wait(bar_full + st * 8, ph);
    {
        const uint32_t wb = sb + OFF_RING + st * STAGE + (warp >> 2) * 16384 + ((mi >> 1) * 8 + r8) * 128 +
                            ((((warp & 3) * 2 + (mi & 1)) ^ r8) << 4);
#pragma unroll
        for (int ks = 0; ks < 8; ks++) ldsm4t(wb + ks * 2048, wf[ks][0], wf[ks][1], wf[ks][2], wf[ks][3]);
    }
    {
        const int src_cta = (c & ~15) | ((warp >> 1) << 2) | mi;
        const int hh = (c >> 2) & 3;
        const uint32_t* po = g_pa + (src_cta * 4 + hh) * kDH + (warp & 1) * 64 + r8 * 8;
        const uint32_t* pm = g_ml + (src_cta * 4 + hh) * 2;
        uint4 v0, v1;
        uint2 ml;
        int it = 0;
        while (true) {
            v0 = ld_rlx4(po);
            v1 = ld_rlx4(po + 4);
            ml = ld_rlx2(pm);
            if (tag_ok(v0, tag) && tag_ok(v1, tag) && (((ml.x ^ tag) | (ml.y ^ tag)) & 1u) == 0) break;
            if (++it > (1 << 21)) __trap();
        }
        __syncwarp();
        TS(12);
        const float ms = __uint_as_float(ml.x);
        float M = fmaxf(ms, __shfl_xor_sync(0xffffffffu, ms, 8));
        M = fmaxf(M, __shfl_xor_sync(0xffffffffu, M, 16));
        const float wgt = ex2((ms - M) * kScaleLog2);
        float L = wgt * __uint_as_float(ml.y);
        L += __shfl_xor_sync(0xffffffffu, L, 8);
        L += __shfl_xor_sync(0xffffffffu, L, 16);
        float v[8] = {__uint_as_float(v0.x), __uint_as_float(v0.y), __uint_as_float(v0.z), __uint_as_float(v0.w),
                      __uint_as_float(v1.x), __uint_as_float(v1.y), __uint_as_float(v1.z), __uint_as_float(v1.w)};
        const float sc = wgt / L;
        float u[4];
        const bool up = (lane & 16) != 0;
#pragma unroll
        for (int e = 0; e < 4; e++) {
            const float keep = (up ? v[e + 4] : v[e]) * sc, send = (up ? v[e] : v[e + 4]) * sc;
            u[e] = keep + __shfl_xor_sync(0xffffffffu, send, 16);
        }
        const bool up2 = (lane & 8) != 0;
        float z[2];
#pragma unroll
        for (int e = 0; e < 2; e++) {
            const float keep = up2 ? u[e + 2] : u[e], send = up2 ? u[e] : u[e + 2];
            z[e] = keep + __shfl_xor_sync(0xffffffffu, send, 8);
        }
        const int dim = (warp & 1) * 64 + r8 * 8 + (up ? 4 : 0) + (up2 ? 2 : 0);
        *reinterpret_cast<uint32_t*>(sp + OFF_Q + ((warp >> 1) * QP + dim) * 2) = pack_bf16(z[0], z[1]);
    }
    bar_consumers();
    {
        const uint32_t oaddr = sb + OFF_Q + ((r8 & 3) * QP + mi * 8) * 2;
        float acc0[4] = {0.f, 0.f, 0.f, 0.f}, acc1[4] = {0.f, 0.f, 0.f, 0.f};
#pragma unroll
        for (int kp = 0; kp < 4; kp++) {
            uint32_t b0, b1, b2, b3;
            ldsm4(oaddr + kp * 64, b0, b1, b2, b3);
            mma16816(acc0, wf[kp * 2][0], wf[kp * 2][1], wf[kp * 2][2], wf[kp * 2][3], b0, b1);
            mma16816(acc1, wf[kp * 2 + 1][0], wf[kp * 2 + 1][1], wf[kp * 2 + 1][2], wf[kp * 2 + 1][3], b2, b3);
        }
        if (jj < 2) {
            uint32_t* dst = g_pb + ((c >> 2) * kB + jj * 2) * kD + (c & 3) * 128 + warp * 16 + rr;
            st_rlx(dst, tagw(acc0[0] + acc1[0], tag));
            st_rlx(dst + kD, tagw(acc0[1] + acc1[1], tag));
            st_rlx(dst + 8, tagw(acc0[2] + acc1[2], tag));
            st_rlx(dst + kD + 8, tagw(acc0[3] + acc1[3], tag));
        }
    }
    TS(13);
    if (warp < 4) {
        const uint4 v = poll4(g_pb + (lane * kB + bf) * kD + col_f, tag);
        __syncwarp();
        TS(14);
        float a[4] = {__uint_as_float(v.x), __uint_as_float(v.y), __uint_as_float(v.z), __uint_as_float(v.w)};
#pragma unroll
        for (int ofs = 16; ofs > 0; ofs >>= 1)
#pragma unroll
            for (int e = 0; e < 4; e++) a[e] += __shfl_xor_sync(0xffffffffu, a[e], ofs);
        if (lane == 0) {
            const float g = misc_f[0];
            uint2 pk;
            pk.x = pack_bf16(g * a[0] + (1.f - g) * fsum[0], g * a[1] + (1.f - g) * fsum[1]);
            pk.y = pack_bf16(g * a[2] + (1.f - g) * fsum[2], g * a[3] + (1.f - g) * fsum[3]);
            *reinterpret_cast<uint2*>(prm.out + bf * kD + col_f) = pk;
            TS(15);
            if (c == 0 && warp == 0) {
                asm volatile("st.relaxed.gpu.global.u32 [%0], %1;" ::"l"(&g_epoch), "r"(epoch + 1u) : "memory");
            }
        }
    }
}

typedef CUresult (*EncodeFn)(CUtensorMap*, CUtensorMapDataType, cuuint32_t, void*, const cuuint64_t*, const cuuint64_t*,
                             const cuuint32_t*, const cuuint32_t*, CUtensorMapInterleave, CUtensorMapSwizzle,
                             CUtensorMapL2promotion, CUtensorMapFloatOOBfill);

void encode2d(EncodeFn enc, CUtensorMap* m, const void* base, uint64_t cols, uint64_t rows, uint64_t pitch_bytes,
              uint32_t box_cols, uint32_t box_rows, CUtensorMapSwizzle swz) {
    cuuint64_t gd[2] = {cols, rows};
    cuuint64_t gs[1] = {pitch_bytes};
    cuuint32_t bd[2] = {box_cols, box_rows};
    cuuint32_t es[2] = {1, 1};
    enc(m, CU_TENSOR_MAP_DATA_TYPE_BFLOAT16, 2, const_cast<void*>(base), gd, gs, bd, es, CU_TENSOR_MAP_INTERLEAVE_NONE,
        swz, CU_TENSOR_MAP_L2_PROMOTION_L2_128B, CU_TENSOR_MAP_FLOAT_OOB_FILL_NONE);
}

}

extern "C" void kernel_launch(void* const* d_in, const int* in_sizes, int n_in, void* d_out, int out_size) {
    (void)in_sizes; (void)n_in; (void)out_size;
    static EncodeFn enc = nullptr;
    if (!enc) {
        void* fn = nullptr;
        cudaDriverEntryPointQueryResult qr;
        cudaGetDriverEntryPoint("cuTensorMapEncodeTiled", &fn, cudaEnableDefault, &qr);
        enc = reinterpret_cast<EncodeFn>(fn);
        cudaFuncSetAttribute(fused_decode_kernel, cudaFuncAttributeMaxDynamicSharedMemorySize, SMEM_BYTES);
    }
    CUtensorMap tk, tv, twq, two, twg, twu, twd;
    encode2d(enc, &tk, d_in[1], 64, (uint64_t)kB * kHKV * kSK * 2, 128, 64, 256, CU_TENSOR_MAP_SWIZZLE_128B);
    encode2d(enc, &tv, d_in[2], 64, (uint64_t)kB * kHKV * kSK * 2, 128, 64, 256, CU_TENSOR_MAP_SWIZZLE_128B);
    encode2d(enc, &twq, d_in[3], kHQ * kDH, kD, kHQ * kDH * 2, 32, 256, CU_TENSOR_MAP_SWIZZLE_64B);
    encode2d(enc, &two, d_in[4], kD, kHQ * kDH, kD * 2, 64, 128, CU_TENSOR_MAP_SWIZZLE_128B);
    encode2d(enc, &twg, d_in[6], kF, kD, kF * 2, 64, 256, CU_TENSOR_MAP_SWIZZLE_128B);
    encode2d(enc, &twu, d_in[7], kF, kD, kF * 2, 64, 256, CU_TENSOR_MAP_SWIZZLE_128B);
    encode2d(enc, &twd, d_in[8], kD, kF, kD * 2, 64, 64, CU_TENSOR_MAP_SWIZZLE_128B);
    Params prm;
    prm.x = reinterpret_cast<const __nv_bfloat16*>(d_in[0]);
    prm.gate_w = reinterpret_cast<const __nv_bfloat16*>(d_in[9]);
    prm.out = reinterpret_cast<__nv_bfloat16*>(d_out);
    fused_decode_kernel<<<NCTA, NTHREADS, SMEM_BYTES>>>(tk, tv, twq, two, twg, twu, twd, prm);
}
```

```cpp
#include <cuda_runtime.h>
#include <cuda_bf16.h>
#include <cuda.h>
#include <stdint.h>

#define EVICT_FIRST 1
#define WIN 2
#define INIT_WRITES 1
#define PACE 1
#define PACE_K 16
#define PACE_L0 (-32)
#define WO_WAIT 1
#define WO_LATE 0
#define PACE_MAX 1200

namespace {

constexpr int kB = 4, kD = 512, kHQ = 32, kHKV = 8, kDH = 128, kSK = 16384, kF = 1792;
constexpr int NATT = 128;
constexpr int NFFN = 4;
constexpr int NCTA = NATT + NFFN;
constexpr int NSTAGE = 6;
constexpr int STAGE = 32768;
constexpr int NCW = 8;
constexpr int NTHREADS = (NCW + 1) * 32;
constexpr int KEYS_PER_CTA = kSK / 4;
constexpr int NT = KEYS_PER_CTA / 128;
constexpr int ATT_STAGES = 2 + 2 * NT;
constexpr int FCOLS = kF / NFFN;
constexpr int FBLK = FCOLS / 64;
constexpr int FFN_STAGES = 4 * FBLK + 2 * FBLK;

constexpr int XP = 520;
constexpr int QP = 136;
constexpr int HP = FCOLS + 8;
constexpr int COMB_W = 544;
constexpr int OFF_RING = 0;
constexpr int OFF_COMB = NSTAGE * STAGE;
constexpr int OFF_X = OFF_COMB + NCW * COMB_W * 4;
constexpr int OFF_Q = OFF_X + kB * XP * 2;
constexpr int OFF_H = OFF_Q + kB * QP * 2;
constexpr int OFF_MX = OFF_H + kB * HP * 2;
constexpr int OFF_L = OFF_MX + NCW * 4 * 4;
constexpr int OFF_MISC = OFF_L + NCW * 4 * 4;
constexpr int OFF_BAR = OFF_MISC + 16;
constexpr int SMEM_USED = OFF_BAR + 2 * NSTAGE * 8;
constexpr int SMEM_BYTES = SMEM_USED + 1024;
static_assert(SMEM_BYTES <= 232448, "smem");
static_assert(OFF_X % 16 == 0 && OFF_Q % 16 == 0 && OFF_H % 16 == 0 && OFF_BAR % 8 == 0, "align");

constexpr float kScaleLog2 = 0.08838834764831845f * 1.4426950408889634f;

__device__ uint32_t g_epoch;
__device__ __align__(128) uint32_t g_prog[2 * 32];
__device__ __align__(128) uint32_t g_q[kB * kHQ * kDH];
__device__ __align__(128) uint32_t g_pa[NATT * 4 * kDH];
__device__ __align__(128) uint32_t g_ml[NATT * 4 * 2];
__device__ __align__(128) uint32_t g_pb[(kHQ + NFFN) * kB * kD];

#define TS(i)
#define TSP(i)

__device__ __forceinline__ uint32_t smem_u32(const void* p) { return (uint32_t)__cvta_generic_to_shared(p); }
__device__ __forceinline__ void mbar_init(uint32_t bar, uint32_t cnt) {
    asm volatile("mbarrier.init.shared::cta.b64 [%0], %1;" ::"r"(bar), "r"(cnt));
}
__device__ __forceinline__ void mbar_expect_tx(uint32_t bar, uint32_t bytes) {
    asm volatile("mbarrier.arrive.expect_tx.shared::cta.b64 _, [%0], %1;" ::"r"(bar), "r"(bytes) : "memory");
}
__device__ __forceinline__ void mbar_arrive(uint32_t bar) {
    asm volatile("mbarrier.arrive.shared::cta.b64 _, [%0];" ::"r"(bar) : "memory");
}
__device__ __forceinline__ bool mbar_try_wait(uint32_t bar, uint32_t parity) {
    uint32_t ok;
    asm volatile("{\n.reg .pred p;\nmbarrier.try_wait.parity.shared::cta.b64 p, [%1], %2;\nselp.u32 %0, 1, 0, p;\n}"
                 : "=r"(ok) : "r"(bar), "r"(parity) : "memory");
    return ok;
}
__device__ __forceinline__ void mbar_wait(uint32_t bar, uint32_t parity) {
    if (mbar_try_wait(bar, parity)) return;
    const long long t0 = clock64();
    while (!mbar_try_wait(bar, parity)) {
        if (clock64() - t0 > 4000000000LL) __trap();
    }
}
__device__ __forceinline__ void tma2d(uint32_t dst, const CUtensorMap* m, int c0, int c1, uint32_t bar) {
    asm volatile("cp.async.bulk.tensor.2d.shared::cluster.global.mbarrier::complete_tx::bytes [%0], [%1, {%3, %4}], [%2];"
                 ::"r"(dst), "l"(m), "r"(bar), "r"(c0), "r"(c1) : "memory");
}
__device__ __forceinline__ void tma2d_hint(uint32_t dst, const CUtensorMap* m, int c0, int c1, uint32_t bar, uint64_t pol) {
    asm volatile("cp.async.bulk.tensor.2d.shared::cluster.global.mbarrier::complete_tx::bytes.L2::cache_hint"
                 " [%0], [%1, {%3, %4}], [%2], %5;"
                 ::"r"(dst), "l"(m), "r"(bar), "r"(c0), "r"(c1), "l"(pol) : "memory");
}
__device__ __forceinline__ void prefetch_tmap(const CUtensorMap* m) {
    asm volatile("prefetch.tensormap [%0];" ::"l"(m) : "memory");
}
__device__ __forceinline__ void ldsm4(uint32_t addr, uint32_t& r0, uint32_t& r1, uint32_t& r2, uint32_t& r3) {
    asm volatile("ldmatrix.sync.aligned.m8n8.x4.shared.b16 {%0,%1,%2,%3}, [%4];"
                 : "=r"(r0), "=r"(r1), "=r"(r2), "=r"(r3) : "r"(addr) : "memory");
}
__device__ __forceinline__ void ldsm4t(uint32_t addr, uint32_t& r0, uint32_t& r1, uint32_t& r2, uint32_t& r3) {
    asm volatile("ldmatrix.sync.aligned.m8n8.x4.trans.shared.b16 {%0,%1,%2,%3}, [%4];"
                 : "=r"(r0), "=r"(r1), "=r"(r2), "=r"(r3) : "r"(addr) : "memory");
}
__device__ __forceinline__ void mma16816(float (&c)[4], uint32_t a0, uint32_t a1, uint32_t a2, uint32_t a3,
                                         uint32_t b0, uint32_t b1) {
    asm volatile("mma.sync.aligned.m16n8k16.row.col.f32.bf16.bf16.f32 {%0,%1,%2,%3}, {%4,%5,%6,%7}, {%8,%9}, {%0,%1,%2,%3};"
                 : "+f"(c[0]), "+f"(c[1]), "+f"(c[2]), "+f"(c[3])
                 : "r"(a0), "r"(a1), "r"(a2), "r"(a3), "r"(b0), "r"(b1));
}
__device__ __forceinline__ float ex2(float x) {
    float y;
    asm("ex2.approx.ftz.f32 %0, %1;" : "=f"(y) : "f"(x));
    return y;
}
__device__ __forceinline__ uint32_t pack_bf16(float lo, float hi) {
    uint32_t r;
    asm("cvt.rn.bf16x2.f32 %0, %1, %2;" : "=r"(r) : "f"(hi), "f"(lo));
    return r;
}
__device__ __forceinline__ float bf16_round(float v) { return __bfloat162float(__float2bfloat16_rn(v)); }
__device__ __forceinline__ void bar_consumers() { asm volatile("bar.sync 1, 256;" ::: "memory"); }

__device__ __forceinline__ uint32_t tagw(float v, uint32_t tag) { return (__float_as_uint(v) & ~1u) | tag; }
__device__ __forceinline__ void st_rlx(uint32_t* p, uint32_t v) {
    asm volatile("st.relaxed.gpu.global.u32 [%0], %1;" ::"l"(p), "r"(v) : "memory");
}
__device__ __forceinline__ void st_rlx2(uint32_t* p, uint32_t a, uint32_t b) {
    asm volatile("st.relaxed.gpu.global.v2.u32 [%0], {%1,%2};" ::"l"(p), "r"(a), "r"(b) : "memory");
}
__device__ __forceinline__ uint4 ld_rlx4(const uint32_t* p) {
    uint4 v;
    asm volatile("ld.relaxed.gpu.global.v4.u32 {%0,%1,%2,%3}, [%4];"
                 : "=r"(v.x), "=r"(v.y), "=r"(v.z), "=r"(v.w) : "l"(p) : "memory");
    return v;
}
__device__ __forceinline__ uint2 ld_rlx2(const uint32_t* p) {
    uint2 v;
    asm volatile("ld.relaxed.gpu.global.v2.u32 {%0,%1}, [%2];" : "=r"(v.x), "=r"(v.y) : "l"(p) : "memory");
    return v;
}
__device__ __forceinline__ bool tag_ok(uint4 v, uint32_t tag) {
    return (((v.x ^ tag) | (v.y ^ tag) | (v.z ^ tag) | (v.w ^ tag)) & 1u) == 0;
}
__device__ __forceinline__ uint4 poll4(const uint32_t* p, uint32_t tag) {
    uint4 v = ld_rlx4(p);
    int it = 0;
    while (!tag_ok(v, tag)) {
        if (++it > (1 << 21)) __trap();
        v = ld_rlx4(p);
    }
    return v;
}

struct Params {
    const __nv_bfloat16* x;
    const __nv_bfloat16* gate_w;
    __nv_bfloat16* out;
};

__global__ void __launch_bounds__(NTHREADS, 1)
fused_decode_kernel(const __grid_constant__ CUtensorMap tm_k, const __grid_constant__ CUtensorMap tm_v,
                    const __grid_constant__ CUtensorMap tm_wq, const __grid_constant__ CUtensorMap tm_wo,
                    const __grid_constant__ CUtensorMap tm_wg, const __grid_constant__ CUtensorMap tm_wu,
                    const __grid_constant__ CUtensorMap tm_wd, const Params prm) {
    extern __shared__ uint8_t smem_raw[];
    const uint32_t sraw = smem_u32(smem_raw);
    const uint32_t sb = (sraw + 1023u) & ~1023u;
    uint8_t* sp = smem_raw + (sb - sraw);
    const int tid = threadIdx.x, warp = tid >> 5, lane = tid & 31;
    const int c = blockIdx.x;
    const bool is_ffn = c >= NATT;
    const uint32_t bar_full = sb + OFF_BAR, bar_empty = bar_full + NSTAGE * 8;

    TS(0);
    if (warp == NCW) {
        if (lane == 0) {
            for (int s = 0; s < NSTAGE; s++) {
                mbar_init(bar_full + s * 8, 1);
                mbar_init(bar_empty + s * 8, NCW);
            }
            asm volatile("fence.mbarrier_init.release.cluster;" ::: "memory");
            asm volatile("fence.proxy.async.shared::cta;" ::: "memory");
        }
        const int nst = is_ffn ? FFN_STAGES : ATT_STAGES;
        const int kv_line0 = (((c >> 2) & 3) * kHKV + (c >> 4)) * (kSK * 2) + (c & 3) * (KEYS_PER_CTA * 2);
        const int f0 = (c - NATT) * FCOLS;
        uint64_t pol;
        asm volatile("createpolicy.fractional.L2::evict_first.b64 %0, 1.0;" : "=l"(pol));
        auto issue = [&](int i, int s) {
            const uint32_t bar = bar_full + s * 8, dst = sb + OFF_RING + s * STAGE;
            mbar_expect_tx(bar, STAGE);
            if (!is_ffn) {
                if (i == 0) {
                    tma2d(dst, &tm_wq, 32 * c, 0, bar);
                    tma2d(dst + STAGE / 2, &tm_wq, 32 * c, 256, bar);
                } else if (i <= 2 * NT) {
                    const int t = (i - 1) >> 1;
                    tma2d_hint(dst, ((i - 1) & 1) ? &tm_v : &tm_k, 0, kv_line0 + t * 256, bar, pol);
                } else {
                    tma2d(dst, &tm_wo, 128 * (c & 3), 128 * (c >> 2), bar);
                    tma2d(dst + STAGE / 2, &tm_wo, 128 * (c & 3) + 64, 128 * (c >> 2), bar);
                }
            } else {
                if (i < 4 * FBLK) {
                    tma2d(dst, (i & 2) ? &tm_wu : &tm_wg, f0 + 64 * (i >> 2), 256 * (i & 1), bar);
                } else {
                    const int ii = i - 4 * FBLK;
#pragma unroll
                    for (int blk = 0; blk < 4; blk++)
                        tma2d(dst + blk * 8192, &tm_wd, 256 * (ii & 1) + 64 * blk, f0 + 64 * (ii >> 1), bar);
                }
            }
        };
        if (lane == 0) {
            TSP(16);
            for (int s = 0; s < WIN; s++) issue(s, s);
            TSP(17);
        }
        __syncthreads();
        if (lane == 0) {
            int s = WIN % NSTAGE, sw = 0;
            uint32_t ph = WIN == NSTAGE ? 0 : 1, phw = 0;
            const uint32_t ep = *reinterpret_cast<volatile uint32_t*>(sp + OFF_MISC + 4);
            uint32_t* prog = g_prog + (ep & 1u) * 32;
            if (c == 0) st_rlx(g_prog + ((ep + 1u) & 1u) * 32, 0u);
            uint32_t r_old = 0;
            int dly = 0;
            for (int i = WIN; i < nst; i++) {
                mbar_wait(bar_full + sw * 8, phw);
                const uint32_t t0 = clock();
                if (!is_ffn && (i & 1)) {
                    if (i >= 5) dly = min(max((64 * (i - 3) - (int)r_old - 1 - (PACE_L0)) * PACE_K, 0), PACE_MAX);
                    asm volatile("atom.relaxed.gpu.global.add.u32 %0, [%1], 1;" : "=r"(r_old) : "l"(prog) : "memory");
                }
                if (i >= NSTAGE) mbar_wait(bar_empty + s * 8, ph);
                if (!is_ffn && i == ATT_STAGES - 1) {
                    const int sv = (ATT_STAGES - 2) % NSTAGE;
                    mbar_wait(bar_full + sv * 8, ((ATT_STAGES - 2) / NSTAGE) & 1);
                }
                while ((int)(clock() - t0) < dly) {}
                issue(i, s);
                if (++s == NSTAGE) { s = 0; ph ^= 1; }
                if (++sw == NSTAGE) { sw = 0; phw ^= 1; }
            }
            TSP(18);
        }
        return;
    }

    {
        const uint4 xv = __ldg(reinterpret_cast<const uint4*>(prm.x) + tid);
        *reinterpret_cast<uint4*>(sp + OFF_X + ((tid >> 6) * XP + (tid & 63) * 8) * 2) = xv;
    }
    float* misc_f = reinterpret_cast<float*>(sp + OFF_MISC);
    uint32_t* misc_u = reinterpret_cast<uint32_t*>(sp + OFF_MISC);
    if (tid == 0) {
        uint32_t e;
        asm volatile("ld.relaxed.gpu.global.u32 %0, [%1];" : "=r"(e) : "l"(&g_epoch) : "memory");
        misc_u[1] = e;
    }
    if (warp == NCW - 1 && !is_ffn) {
        const int bf = c >> 5;
        const uint4* xp = reinterpret_cast<const uint4*>(prm.x + bf * kD) + lane * 2;
        const uint4* gp = reinterpret_cast<const uint4*>(prm.gate_w) + lane * 2;
        float acc = 0.f;
#pragma unroll
        for (int u = 0; u < 2; u++) {
            const uint4 a = __ldg(xp + u), g = __ldg(gp + u);
            const uint32_t aw[4] = {a.x, a.y, a.z, a.w}, gw[4] = {g.x, g.y, g.z, g.w};
#pragma unroll
            for (int e = 0; e < 4; e++) {
                acc = fmaf(__uint_as_float(aw[e] << 16), __uint_as_float(gw[e] << 16), acc);
                acc = fmaf(__uint_as_float(aw[e] & 0xffff0000u), __uint_as_float(gw[e] & 0xffff0000u), acc);
            }
        }
#pragma unroll
        for (int o = 16; o > 0; o >>= 1) acc += __shfl_xor_sync(0xffffffffu, acc, o);
        if (lane == 0) misc_f[0] = 1.f / (1.f + __expf(-acc));
    }
    __syncthreads();
    TS(1);
    const uint32_t epoch = misc_u[1];
    const uint32_t tag = (epoch + 1u) & 1u;

    const int r8 = lane & 7, mi = lane >> 3;
    const int rr = lane >> 2, jj = lane & 3;
    int st = 0;
    uint32_t ph = 0;
    auto advance = [&]() { if (++st == NSTAGE) { st = 0; ph ^= 1; } };
    auto release = [&]() {
        __syncwarp();
        if (lane == 0) mbar_arrive(bar_empty + st * 8);
        advance();
    };
    const uint32_t x_addr = sb + OFF_X + ((r8 & 3) * XP + mi * 8) * 2;

    if (is_ffn) {
        const int fi = c - NATT;
        if (lane < 16) {
            uint32_t* dst = g_pb + ((kHQ + fi) * kB + rr) * kD + (warp >> 1) * 64 + (warp & 1) * 32 + jj * 2;
#pragma unroll
            for (int ch = 0; ch < 2; ch++)
#pragma unroll
                for (int n = 0; n < 4; n++) st_rlx2(dst + ch * 256 + n * 8, tag ^ 1u, tag ^ 1u);
        }
        for (int jb = 0; jb < FBLK; jb++) {
            float gu[2][2][4];
#pragma unroll
            for (int m = 0; m < 2; m++) {
#pragma unroll
                for (int e = 0; e < 4; e++) gu[m][0][e] = gu[m][1][e] = 0.f;
#pragma unroll
                for (int kh = 0; kh < 2; kh++) {
                    mbar_wait(bar_full + st * 8, ph);
                    const uint32_t wb = sb + OFF_RING + st * STAGE + lane * 128 + ((warp ^ r8) << 4);
#pragma unroll
                    for (int kk = 0; kk < 8; kk++) {
                        uint32_t b0, b1, b2, b3, a0, a1, a2, a3;
                        ldsm4t(wb + kk * 4096, b0, b1, b2, b3);
                        ldsm4(x_addr + (kh * 256 + kk * 32) * 2, a0, a1, a2, a3);
                        mma16816(gu[m][0], a0, 0u, a1, 0u, b0, b1);
                        mma16816(gu[m][1], a2, 0u, a3, 0u, b2, b3);
                    }
                    release();
                }
            }
            const float g0 = bf16_round(gu[0][0][0] + gu[0][1][0]), g1 = bf16_round(gu[0][0][1] + gu[0][1][1]);
            const float u0 = bf16_round(gu[1][0][0] + gu[1][1][0]), u1 = bf16_round(gu[1][0][1] + gu[1][1][1]);
            const float h0 = (g0 > 0.f ? g0 : 0.f) * u0, h1 = (g1 > 0.f ? g1 : 0.f) * u1;
            if (lane < 16)
                *reinterpret_cast<uint32_t*>(sp + OFF_H + (rr * HP + jb * 64 + warp * 8 + jj * 2) * 2) = pack_bf16(h0, h1);
        }
        bar_consumers();
        TS(10);
        float acc[2][4][4];
#pragma unroll
        for (int ch = 0; ch < 2; ch++)
#pragma unroll
            for (int n = 0; n < 4; n++)
#pragma unroll
                for (int e = 0; e < 4; e++) acc[ch][n][e] = 0.f;
        const uint32_t h_addr = sb + OFF_H + ((r8 & 3) * HP + mi * 8) * 2;
        for (int jb = 0; jb < FBLK; jb++) {
            uint32_t a[8];
            ldsm4(h_addr + (jb * 64) * 2, a[0], a[1], a[2], a[3]);
            ldsm4(h_addr + (jb * 64 + 32) * 2, a[4], a[5], a[6], a[7]);
#pragma unroll
            for (int ch = 0; ch < 2; ch++) {
                mbar_wait(bar_full + st * 8, ph);
                const uint32_t wb = sb + OFF_RING + st * STAGE + (warp >> 1) * 8192 + (lane & 15) * 128;
#pragma unroll
                for (int ks = 0; ks < 4; ks++) {
#pragma unroll
                    for (int np = 0; np < 2; np++) {
                        uint32_t b0, b1, b2, b3;
                        const int chunk = (warp & 1) * 4 + np * 2 + (lane >> 4);
                        ldsm4t(wb + ks * 2048 + ((chunk ^ r8) << 4), b0, b1, b2, b3);
                        mma16816(acc[ch][np * 2], a[ks * 2], 0u, a[ks * 2 + 1], 0u, b0, b1);
                        mma16816(acc[ch][np * 2 + 1], a[ks * 2], 0u, a[ks * 2 + 1], 0u, b2, b3);
                    }
                }
                release();
            }
        }
        if (lane < 16) {
            uint32_t* dst = g_pb + ((kHQ + fi) * kB + rr) * kD + (warp >> 1) * 64 + (warp & 1) * 32 + jj * 2;
#pragma unroll
            for (int ch = 0; ch < 2; ch++)
#pragma unroll
                for (int n = 0; n < 4; n++)
                    st_rlx2(dst + ch * 256 + n * 8, tagw(acc[ch][n][0], tag), tagw(acc[ch][n][1], tag));
        }
        TS(15);
        return;
    }

    float* comb = reinterpret_cast<float*>(sp + OFF_COMB);
    float* mx_s = reinterpret_cast<float*>(sp + OFF_MX);
    float* l_s = reinterpret_cast<float*>(sp + OFF_L);
    const int hkv = c >> 4, batch = (c >> 2) & 3;
    {
        const uint32_t nr = tag ^ 1u;
        if (tid < 128) st_rlx(g_q + (tid >> 5) * (kHQ * kDH) + 32 * c + (tid & 31), nr);
        uint32_t* dst = g_pa + (c * 4 + (tid & 1) * 2) * kDH + (tid >> 1);
        st_rlx(dst, nr);
        st_rlx(dst + kDH, nr);
        if (tid < 4) st_rlx2(g_ml + (c * 4 + tid) * 2, nr, nr);
        if (jj < 2) {
            uint32_t* d2 = g_pb + ((c >> 2) * kB + jj * 2) * kD + (c & 3) * 128 + warp * 16 + rr;
            st_rlx(d2, nr);
            st_rlx(d2 + kD, nr);
            st_rlx(d2 + 8, nr);
            st_rlx(d2 + kD + 8, nr);
        }
    }

    {
        float qc[4][4];
#pragma unroll
        for (int n = 0; n < 4; n++)
#pragma unroll
            for (int e = 0; e < 4; e++) qc[n][e] = 0.f;
        uint32_t a[8];
        ldsm4(x_addr + (warp * 64) * 2, a[0], a[1], a[2], a[3]);
        ldsm4(x_addr + (warp * 64 + 32) * 2, a[4], a[5], a[6], a[7]);
        mbar_wait(bar_full + st * 8, ph);
        TS(2);
#pragma unroll
        for (int ks = 0; ks < 4; ks++) {
            const int row = warp * 64 + ks * 16 + (lane & 15);
#pragma unroll
            for (int np = 0; np < 2; np++) {
                uint32_t b0, b1, b2, b3;
                const int chunk = np * 2 + (lane >> 4);
                ldsm4t(sb + OFF_RING + st * STAGE + row * 64 + ((chunk ^ ((row >> 1) & 3)) << 4), b0, b1, b2, b3);
                mma16816(qc[np * 2], a[ks * 2], 0u, a[ks * 2 + 1], 0u, b0, b1);
                mma16816(qc[np * 2 + 1], a[ks * 2], 0u, a[ks * 2 + 1], 0u, b2, b3);
            }
        }
        release();
        if (lane < 16) {
#pragma unroll
            for (int n = 0; n < 4; n++)
                *reinterpret_cast<float2*>(comb + warp * 128 + rr * 32 + n * 8 + jj * 2) = make_float2(qc[n][0], qc[n][1]);
        }
        bar_consumers();
        if (tid < 128) {
            float s = 0.f;
#pragma unroll
            for (int w = 0; w < NCW; w++) s += comb[w * 128 + tid];
            st_rlx(g_q + (tid >> 5) * (kHQ * kDH) + 32 * c + (tid & 31), tagw(s, tag));
            TS(3);
            const uint32_t* qsrc = g_q + batch * (kHQ * kDH) + hkv * 512 + tid * 4;
            uint4 v = ld_rlx4(qsrc);
            int it = 0;
            while (!tag_ok(v, tag)) {
                if (++it > (1 << 21)) __trap();
                __nanosleep(64);
                v = ld_rlx4(qsrc);
            }
            uint2 pk;
            pk.x = pack_bf16(__uint_as_float(v.x), __uint_as_float(v.y));
            pk.y = pack_bf16(__uint_as_float(v.z), __uint_as_float(v.w));
            *reinterpret_cast<uint2*>(sp + OFF_Q + ((tid >> 5) * QP + (tid & 31) * 4) * 2) = pk;
        }
        bar_consumers();
    }
    TS(4);
    uint32_t qa[8];
    {
        const uint32_t qaddr = sb + OFF_Q + ((r8 & 3) * QP + (r8 >> 2) * 64 + mi * 8) * 2;
        ldsm4(qaddr, qa[0], qa[1], qa[2], qa[3]);
        ldsm4(qaddr + 64, qa[4], qa[5], qa[6], qa[7]);
    }

    float o[4][4];
#pragma unroll
    for (int m = 0; m < 4; m++)
#pragma unroll
        for (int e = 0; e < 4; e++) o[m][e] = 0.f;
    float m_run = -INFINITY, l_run = 0.f;
    const uint32_t k_off = (warp * 32 + r8) * 128 + ((mi ^ r8) << 4);
    const uint32_t v_off = (warp * 32 + (mi >> 1) * 8 + r8) * 128 + (((mi & 1) ^ r8) << 4);
    const uint32_t pmask = lane < 16 ? 0x0000ffffu : 0xffff0000u;
    float fsum[4] = {0.f, 0.f, 0.f, 0.f};
    const int bf = c >> 5, col_f = (c & 31) * 16 + (warp & 3) * 4;

    for (int t = 0; t < NT; t++) {
        float s[4][4];
        mbar_wait(bar_full + st * 8, ph);
        {
            const uint32_t kb = sb + OFF_RING + st * STAGE;
#pragma unroll
            for (int g = 0; g < 4; g++) {
#pragma unroll
                for (int e = 0; e < 4; e++) s[g][e] = 0.f;
                uint32_t b0, b1, b2, b3;
                ldsm4(kb + k_off + g * 1024, b0, b1, b2, b3);
                mma16816(s[g], qa[0], 0u, qa[1], 0u, b0, b1);
                mma16816(s[g], qa[2], 0u, qa[3], 0u, b2, b3);
                ldsm4(kb + (k_off ^ 64u) + g * 1024, b0, b1, b2, b3);
                mma16816(s[g], qa[4], 0u, qa[5], 0u, b0, b1);
                mma16816(s[g], qa[6], 0u, qa[7], 0u, b2, b3);
            }
        }
        release();
        float sc[4];
#pragma unroll
        for (int g = 0; g < 4; g++) {
            const float v = lane < 16 ? s[g][0] : s[g][1];
            sc[g] = v + __shfl_xor_sync(0xffffffffu, v, 16);
        }
        float mx = fmaxf(fmaxf(sc[0], sc[1]), fmaxf(sc[2], sc[3]));
        mx = fmaxf(mx, __shfl_xor_sync(0xffffffffu, mx, 1));
        mx = fmaxf(mx, __shfl_xor_sync(0xffffffffu, mx, 2));
        float m_new = fmaxf(m_run, mx);
        if (t == NT - 1) {
            if (lane < 16 && jj == 0) mx_s[warp * 4 + rr] = m_new;
            bar_consumers();
#pragma unroll
            for (int w = 0; w < NCW; w++) m_new = fmaxf(m_new, mx_s[w * 4 + (rr & 3)]);
        }
        if (__any_sync(0xffffffffu, m_new > m_run)) {
            const float alpha = ex2((m_run - m_new) * kScaleLog2);
            l_run *= alpha;
            const float a0 = __shfl_sync(0xffffffffu, alpha, ((2 * jj) & 3) * 4);
            const float a1 = __shfl_sync(0xffffffffu, alpha, ((2 * jj + 1) & 3) * 4);
#pragma unroll
            for (int m = 0; m < 4; m++) {
                o[m][0] *= a0; o[m][1] *= a1; o[m][2] *= a0; o[m][3] *= a1;
            }
            m_run = m_new;
        }
        const float mc = m_run * kScaleLog2;
        uint32_t pb[4];
#pragma unroll
        for (int g = 0; g < 4; g++) {
            const float p = ex2(fmaf(sc[g], kScaleLog2, -mc));
            l_run += p;
            pb[g] = pack_bf16(p, p) & pmask;
        }
        if (t == NT - 4 && warp < 4) {
            uint4 v = make_uint4(0, 0, 0, 0);
            if (lane < NFFN) v = poll4(g_pb + ((kHQ + lane) * kB + bf) * kD + col_f, tag);
            __syncwarp();
            fsum[0] = __uint_as_float(v.x); fsum[1] = __uint_as_float(v.y);
            fsum[2] = __uint_as_float(v.z); fsum[3] = __uint_as_float(v.w);
#pragma unroll
            for (int e = 0; e < 4; e++) {
                fsum[e] += __shfl_xor_sync(0xffffffffu, fsum[e], 1);
                fsum[e] += __shfl_xor_sync(0xffffffffu, fsum[e], 2);
            }
        }
        mbar_wait(bar_full + st * 8, ph);
        {
            const uint32_t vb = sb + OFF_RING + st * STAGE;
#pragma unroll
            for (int oc = 0; oc < 2; oc++) {
#pragma unroll
                for (int m = 0; m < 4; m++) {
                    uint32_t a0, a1, a2, a3;
                    ldsm4t(vb + ((v_off + oc * 2048) ^ (m * 32)), a0, a1, a2, a3);
                    mma16816(o[m], a0, a1, a2, a3, pb[oc * 2], pb[oc * 2 + 1]);
                }
            }
        }
        release();
    }

    TS(10);
    l_run += __shfl_xor_sync(0xffffffffu, l_run, 1);
    l_run += __shfl_xor_sync(0xffffffffu, l_run, 2);
    if (lane < 16 && jj == 0) l_s[warp * 4 + rr] = l_run;
    {
        float* dst = comb + warp * COMB_W + (jj >> 1) * 272 + rr * 4 + (jj & 1) * 2;
#pragma unroll
        for (int m = 0; m < 4; m++) {
            *reinterpret_cast<float2*>(dst + m * 64) = make_float2(o[m][0], o[m][1]);
            *reinterpret_cast<float2*>(dst + m * 64 + 32) = make_float2(o[m][2], o[m][3]);
        }
    }
    bar_consumers();
    {
        const float* src = comb + (tid >> 7) * 272 + (tid & 127) * 2;
        float2 acc = *reinterpret_cast<const float2*>(src);
#pragma unroll
        for (int w = 1; w < NCW; w++) {
            const float2 v = *reinterpret_cast<const float2*>(src + w * COMB_W);
            acc.x += v.x; acc.y += v.y;
        }
        uint32_t* dst = g_pa + (c * 4 + (tid & 1) * 2) * kDH + (tid >> 1);
        st_rlx(dst, tagw(acc.x, tag));
        st_rlx(dst + kDH, tagw(acc.y, tag));
        if (tid < 4) {
            float l = 0.f, m = mx_s[tid];
#pragma unroll
            for (int w = 0; w < NCW; w++) { l += l_s[w * 4 + tid]; m = fmaxf(m, mx_s[w * 4 + tid]); }
            st_rlx2(g_ml + (c * 4 + tid) * 2, tagw(m, tag), tagw(l, tag));
        }
    }

    TS(11);
    uint32_t wf[8][4];
    auto load_wo = [&]() {
        mbar_wait(bar_full + st * 8, ph);
        const uint32_t wb = sb + OFF_RING + st * STAGE + (warp >> 2) * 16384 + ((mi >> 1) * 8 + r8) * 128 +
                            ((((warp & 3) * 2 + (mi & 1)) ^ r8) << 4);
#pragma unroll
        for (int ks = 0; ks < 8; ks++) ldsm4t(wb + ks * 2048, wf[ks][0], wf[ks][1], wf[ks][2], wf[ks][3]);
    };
    load_wo();
    {
        const int src_cta = (c & ~15) | ((warp >> 1) << 2) | mi;
        const int hh = (c >> 2) & 3;
        const uint32_t* po = g_pa + (src_cta * 4 + hh) * kDH + (warp & 1) * 64 + r8 * 8;
        const uint32_t* pm = g_ml + (src_cta * 4 + hh) * 2;
        uint4 v0, v1;
        uint2 ml;
        int it = 0;
        while (true) {
            v0 = ld_rlx4(po);
            v1 = ld_rlx4(po + 4);
            ml = ld_rlx2(pm);
            if (tag_ok(v0, tag) && tag_ok(v1, tag) && (((ml.x ^ tag) | (ml.y ^ tag)) & 1u) == 0) break;
            if (++it > (1 << 21)) __trap();
        }
        __syncwarp();
        TS(12);
        const float ms = __uint_as_float(ml.x);
        float M = fmaxf(ms, __shfl_xor_sync(0xffffffffu, ms, 8));
        M = fmaxf(M, __shfl_xor_sync(0xffffffffu, M, 16));
        const float wgt = ex2((ms - M) * kScaleLog2);
        float L = wgt * __uint_as_float(ml.y);
        L += __shfl_xor_sync(0xffffffffu, L, 8);
        L += __shfl_xor_sync(0xffffffffu, L, 16);
        float v[8] = {__uint_as_float(v0.x), __uint_as_float(v0.y), __uint_as_float(v0.z), __uint_as_float(v0.w),
                      __uint_as_float(v1.x), __uint_as_float(v1.y), __uint_as_float(v1.z), __uint_as_float(v1.w)};
        const float sc = wgt / L;
        float u[4];
        const bool up = (lane & 16) != 0;
#pragma unroll
        for (int e = 0; e < 4; e++) {
            const float keep = (up ? v[e + 4] : v[e]) * sc, send = (up ? v[e] : v[e + 4]) * sc;
            u[e] = keep + __shfl_xor_sync(0xffffffffu, send, 16);
        }
        const bool up2 = (lane & 8) != 0;
        float z[2];
#pragma unroll
        for (int e = 0; e < 2; e++) {
            const float keep = up2 ? u[e + 2] : u[e], send = up2 ? u[e] : u[e + 2];
            z[e] = keep + __shfl_xor_sync(0xffffffffu, send, 8);
        }
        const int dim = (warp & 1) * 64 + r8 * 8 + (up ? 4 : 0) + (up2 ? 2 : 0);
        *reinterpret_cast<uint32_t*>(sp + OFF_Q + ((warp >> 1) * QP + dim) * 2) = pack_bf16(z[0], z[1]);
    }
    bar_consumers();
    {
        const uint32_t oaddr = sb + OFF_Q + ((r8 & 3) * QP + mi * 8) * 2;
        float acc0[4] = {0.f, 0.f, 0.f, 0.f}, acc1[4] = {0.f, 0.f, 0.f, 0.f};
#pragma unroll
        for (int kp = 0; kp < 4; kp++) {
            uint32_t b0, b1, b2, b3;
            ldsm4(oaddr + kp * 64, b0, b1, b2, b3);
            mma16816(acc0, wf[kp * 2][0], wf[kp * 2][1], wf[kp * 2][2], wf[kp * 2][3], b0, b1);
            mma16816(acc1, wf[kp * 2 + 1][0], wf[kp * 2 + 1][1], wf[kp * 2 + 1][2], wf[kp * 2 + 1][3], b2, b3);
        }
        if (jj < 2) {
            uint32_t* dst = g_pb + ((c >> 2) * kB + jj * 2) * kD + (c & 3) * 128 + warp * 16 + rr;
            st_rlx(dst, tagw(acc0[0] + acc1[0], tag));
            st_rlx(dst + kD, tagw(acc0[1] + acc1[1], tag));
            st_rlx(dst + 8, tagw(acc0[2] + acc1[2], tag));
            st_rlx(dst + kD + 8, tagw(acc0[3] + acc1[3], tag));
        }
    }
    TS(13);
    if (warp < 4) {
        const uint4 v = poll4(g_pb + (lane * kB + bf) * kD + col_f, tag);
        __syncwarp();
        TS(14);
        float a[4] = {__uint_as_float(v.x), __uint_as_float(v.y), __uint_as_float(v.z), __uint_as_float(v.w)};
#pragma unroll
        for (int ofs = 16; ofs > 0; ofs >>= 1)
#pragma unroll
            for (int e = 0; e < 4; e++) a[e] += __shfl_xor_sync(0xffffffffu, a[e], ofs);
        if (lane == 0) {
            const float g = misc_f[0];
            uint2 pk;
            pk.x = pack_bf16(g * a[0] + (1.f - g) * fsum[0], g * a[1] + (1.f - g) * fsum[1]);
            pk.y = pack_bf16(g * a[2] + (1.f - g) * fsum[2], g * a[3] + (1.f - g) * fsum[3]);
            *reinterpret_cast<uint2*>(prm.out + bf * kD + col_f) = pk;
            TS(15);
            if (c == 0 && warp == 0) {
                asm volatile("st.relaxed.gpu.global.u32 [%0], %1;" ::"l"(&g_epoch), "r"(epoch + 1u) : "memory");
            }
        }
    }
}

typedef CUresult (*EncodeFn)(CUtensorMap*, CUtensorMapDataType, cuuint32_t, void*, const cuuint64_t*, const cuuint64_t*,
                             const cuuint32_t*, const cuuint32_t*, CUtensorMapInterleave, CUtensorMapSwizzle,
                             CUtensorMapL2promotion, CUtensorMapFloatOOBfill);

void encode2d(EncodeFn enc, CUtensorMap* m, const void* base, uint64_t cols, uint64_t rows, uint64_t pitch_bytes,
              uint32_t box_cols, uint32_t box_rows, CUtensorMapSwizzle swz) {
    cuuint64_t gd[2] = {cols, rows};
    cuuint64_t gs[1] = {pitch_bytes};
    cuuint32_t bd[2] = {box_cols, box_rows};
    cuuint32_t es[2] = {1, 1};
    enc(m, CU_TENSOR_MAP_DATA_TYPE_BFLOAT16, 2, const_cast<void*>(base), gd, gs, bd, es, CU_TENSOR_MAP_INTERLEAVE_NONE,
        swz, CU_TENSOR_MAP_L2_PROMOTION_L2_128B, CU_TENSOR_MAP_FLOAT_OOB_FILL_NONE);
}

}

extern "C" void kernel_launch(void* const* d_in, const int* in_sizes, int n_in, void* d_out, int out_size) {
    (void)in_sizes; (void)n_in; (void)out_size;
    static EncodeFn enc = nullptr;
    if (!enc) {
        void* fn = nullptr;
        cudaDriverEntryPointQueryResult qr;
        cudaGetDriverEntryPoint("cuTensorMapEncodeTiled", &fn, cudaEnableDefault, &qr);
        enc = reinterpret_cast<EncodeFn>(fn);
        cudaFuncSetAttribute(fused_decode_kernel, cudaFuncAttributeMaxDynamicSharedMemorySize, SMEM_BYTES);
    }
    CUtensorMap tk, tv, twq, two, twg, twu, twd;
    encode2d(enc, &tk, d_in[1], 64, (uint64_t)kB * kHKV * kSK * 2, 128, 64, 256, CU_TENSOR_MAP_SWIZZLE_128B);
    encode2d(enc, &tv, d_in[2], 64, (uint64_t)kB * kHKV * kSK * 2, 128, 64, 256, CU_TENSOR_MAP_SWIZZLE_128B);
    encode2d(enc, &twq, d_in[3], kHQ * kDH, kD, kHQ * kDH * 2, 32, 256, CU_TENSOR_MAP_SWIZZLE_64B);
    encode2d(enc, &two, d_in[4], kD, kHQ * kDH, kD * 2, 64, 128, CU_TENSOR_MAP_SWIZZLE_128B);
    encode2d(enc, &twg, d_in[6], kF, kD, kF * 2, 64, 256, CU_TENSOR_MAP_SWIZZLE_128B);
    encode2d(enc, &twu, d_in[7], kF, kD, kF * 2, 64, 256, CU_TENSOR_MAP_SWIZZLE_128B);
    encode2d(enc, &twd, d_in[8], kD, kF, kD * 2, 64, 64, CU_TENSOR_MAP_SWIZZLE_128B);
    Params prm;
    prm.x = reinterpret_cast<const __nv_bfloat16*>(d_in[0]);
    prm.gate_w = reinterpret_cast<const __nv_bfloat16*>(d_in[9]);
    prm.out = reinterpret_cast<__nv_bfloat16*>(d_out);
    fused_decode_kernel<<<NCTA, NTHREADS, SMEM_BYTES>>>(tk, tv, twq, two, twg, twu, twd, prm);
}
```

```cpp
#include <cuda_runtime.h>
#include <cuda_bf16.h>
#include <cuda.h>
#include <stdint.h>

#define EVICT_FIRST 1
#define WIN 2
#define INIT_WRITES 1
#define PACE 1
#define PACE_K 16
#define PACE_L0 (-32)
#define PACE_MAX 2000
#define WO_AT 7
#define NPOLL_A 1
#define NPOLL_B 1
#define POLL_GAP_A 300
#define POLL_GAP_B 170
#define DLY_A 600
#define PRED_A 0
#define SPEC_A 0

namespace {

constexpr int kB = 4, kD = 512, kHQ = 32, kHKV = 8, kDH = 128, kSK = 16384, kF = 1792;
constexpr int NATT = 128;
constexpr int NFFN = 4;
constexpr int NCTA = NATT + NFFN;
constexpr int NSTAGE = 6;
constexpr int STAGE = 32768;
constexpr int NCW = 8;
constexpr int NTHREADS = (NCW + 1) * 32;
constexpr int KEYS_PER_CTA = kSK / 4;
constexpr int NT = KEYS_PER_CTA / 128;
constexpr int ATT_STAGES = 2 + 2 * NT;
constexpr int FCOLS = kF / NFFN;
constexpr int FBLK = FCOLS / 64;
constexpr int FFN_STAGES = 4 * FBLK + 2 * FBLK;

constexpr int XP = 520;
constexpr int QP = 136;
constexpr int HP = FCOLS + 8;
constexpr int COMB_W = 640;
constexpr int OFF_RING = 0;
constexpr int OFF_COMB = NSTAGE * STAGE;
constexpr int OFF_X = OFF_COMB + NCW * COMB_W * 4;
constexpr int OFF_Q = OFF_X + kB * XP * 2;
constexpr int OFF_H = OFF_Q + kB * QP * 2;
constexpr int OFF_MX = OFF_H + kB * HP * 2;
constexpr int OFF_L = OFF_MX + NCW * 4 * 4;
constexpr int OFF_MISC = OFF_L + NCW * 4 * 4;
constexpr int OFF_BAR = OFF_MISC + 16;
constexpr int NVP = 8;
constexpr int SMEM_USED = OFF_BAR + (2 * NSTAGE + NVP) * 8;
constexpr int SMEM_BYTES = SMEM_USED + 1024;
static_assert(SMEM_BYTES <= 232448, "smem");
static_assert(OFF_X % 16 == 0 && OFF_Q % 16 == 0 && OFF_H % 16 == 0 && OFF_BAR % 8 == 0, "align");

constexpr float kScaleLog2 = 0.08838834764831845f * 1.4426950408889634f;

__device__ uint32_t g_epoch;
__device__ __align__(128) uint32_t g_prog[2 * 32];
__device__ __align__(128) uint32_t g_q[kB * kHQ * kDH];
__device__ __align__(128) uint32_t g_pa[NATT * 4 * kDH];
__device__ __align__(128) uint32_t g_ml[NATT * 4 * 2];
__device__ __align__(128) uint32_t g_pb[(kHQ + NFFN) * kB * kD];

#define TS(i)
#define TSP(i)

__device__ __forceinline__ uint32_t smem_u32(const void* p) { return (uint32_t)__cvta_generic_to_shared(p); }
__device__ __forceinline__ void mbar_init(uint32_t bar, uint32_t cnt) {
    asm volatile("mbarrier.init.shared::cta.b64 [%0], %1;" ::"r"(bar), "r"(cnt));
}
__device__ __forceinline__ void mbar_expect_tx(uint32_t bar, uint32_t bytes) {
    asm volatile("mbarrier.arrive.expect_tx.shared::cta.b64 _, [%0], %1;" ::"r"(bar), "r"(bytes) : "memory");
}
__device__ __forceinline__ void mbar_arrive(uint32_t bar) {
    asm volatile("mbarrier.arrive.shared::cta.b64 _, [%0];" ::"r"(bar) : "memory");
}
__device__ __forceinline__ bool mbar_try_wait(uint32_t bar, uint32_t parity) {
    uint32_t ok;
    asm volatile("{\n.reg .pred p;\nmbarrier.try_wait.parity.shared::cta.b64 p, [%1], %2;\nselp.u32 %0, 1, 0, p;\n}"
                 : "=r"(ok) : "r"(bar), "r"(parity) : "memory");
    return ok;
}
__device__ __forceinline__ void mbar_wait(uint32_t bar, uint32_t parity) {
    if (mbar_try_wait(bar, parity)) return;
    const long long t0 = clock64();
    while (!mbar_try_wait(bar, parity)) {
        if (clock64() - t0 > 4000000000LL) __trap();
    }
}
__device__ __forceinline__ void tma2d(uint32_t dst, const CUtensorMap* m, int c0, int c1, uint32_t bar) {
    asm volatile("cp.async.bulk.tensor.2d.shared::cluster.global.mbarrier::complete_tx::bytes [%0], [%1, {%3, %4}], [%2];"
                 ::"r"(dst), "l"(m), "r"(bar), "r"(c0), "r"(c1) : "memory");
}
__device__ __forceinline__ void tma2d_hint(uint32_t dst, const CUtensorMap* m, int c0, int c1, uint32_t bar, uint64_t pol) {
    asm volatile("cp.async.bulk.tensor.2d.shared::cluster.global.mbarrier::complete_tx::bytes.L2::cache_hint"
                 " [%0], [%1, {%3, %4}], [%2], %5;"
                 ::"r"(dst), "l"(m), "r"(bar), "r"(c0), "r"(c1), "l"(pol) : "memory");
}
__device__ __forceinline__ void prefetch_tmap(const CUtensorMap* m) {
    asm volatile("prefetch.tensormap [%0];" ::"l"(m) : "memory");
}
__device__ __forceinline__ void ldsm4(uint32_t addr, uint32_t& r0, uint32_t& r1, uint32_t& r2, uint32_t& r3) {
    asm volatile("ldmatrix.sync.aligned.m8n8.x4.shared.b16 {%0,%1,%2,%3}, [%4];"
                 : "=r"(r0), "=r"(r1), "=r"(r2), "=r"(r3) : "r"(addr) : "memory");
}
__device__ __forceinline__ void ldsm4t(uint32_t addr, uint32_t& r0, uint32_t& r1, uint32_t& r2, uint32_t& r3) {
    asm volatile("ldmatrix.sync.aligned.m8n8.x4.trans.shared.b16 {%0,%1,%2,%3}, [%4];"
                 : "=r"(r0), "=r"(r1), "=r"(r2), "=r"(r3) : "r"(addr) : "memory");
}
__device__ __forceinline__ void mma16816(float (&c)[4], uint32_t a0, uint32_t a1, uint32_t a2, uint32_t a3,
                                         uint32_t b0, uint32_t b1) {
    asm volatile("mma.sync.aligned.m16n8k16.row.col.f32.bf16.bf16.f32 {%0,%1,%2,%3}, {%4,%5,%6,%7}, {%8,%9}, {%0,%1,%2,%3};"
                 : "+f"(c[0]), "+f"(c[1]), "+f"(c[2]), "+f"(c[3])
                 : "r"(a0), "r"(a1), "r"(a2), "r"(a3), "r"(b0), "r"(b1));
}
__device__ __forceinline__ float ex2(float x) {
    float y;
    asm("ex2.approx.ftz.f32 %0, %1;" : "=f"(y) : "f"(x));
    return y;
}
__device__ __forceinline__ uint32_t pack_bf16(float lo, float hi) {
    uint32_t r;
    asm("cvt.rn.bf16x2.f32 %0, %1, %2;" : "=r"(r) : "f"(hi), "f"(lo));
    return r;
}
__device__ __forceinline__ float bf16_round(float v) { return __bfloat162float(__float2bfloat16_rn(v)); }
__device__ __forceinline__ void bar_consumers() { asm volatile("bar.sync 1, 256;" ::: "memory"); }

__device__ __forceinline__ uint32_t tagw(float v, uint32_t tag) { return (__float_as_uint(v) & ~1u) | tag; }
__device__ __forceinline__ void st_rlx(uint32_t* p, uint32_t v) {
    asm volatile("st.relaxed.gpu.global.u32 [%0], %1;" ::"l"(p), "r"(v) : "memory");
}
__device__ __forceinline__ void st_rlx2(uint32_t* p, uint32_t a, uint32_t b) {
    asm volatile("st.relaxed.gpu.global.v2.u32 [%0], {%1,%2};" ::"l"(p), "r"(a), "r"(b) : "memory");
}
__device__ __forceinline__ uint4 ld_rlx4(const uint32_t* p) {
    uint4 v;
    asm volatile("ld.relaxed.gpu.global.v4.u32 {%0,%1,%2,%3}, [%4];"
                 : "=r"(v.x), "=r"(v.y), "=r"(v.z), "=r"(v.w) : "l"(p) : "memory");
    return v;
}
__device__ __forceinline__ uint2 ld_rlx2(const uint32_t* p) {
    uint2 v;
    asm volatile("ld.relaxed.gpu.global.v2.u32 {%0,%1}, [%2];" : "=r"(v.x), "=r"(v.y) : "l"(p) : "memory");
    return v;
}
__device__ __forceinline__ bool tag_ok(uint4 v, uint32_t tag) {
    return (((v.x ^ tag) | (v.y ^ tag) | (v.z ^ tag) | (v.w ^ tag)) & 1u) == 0;
}
__device__ __forceinline__ uint4 poll4(const uint32_t* p, uint32_t tag) {
    uint4 v = ld_rlx4(p);
    int it = 0;
    while (!tag_ok(v, tag)) {
        if (++it > (1 << 21)) __trap();
        v = ld_rlx4(p);
    }
    return v;
}

struct Params {
    const __nv_bfloat16* x;
    const __nv_bfloat16* gate_w;
    __nv_bfloat16* out;
};

__global__ void __launch_bounds__(NTHREADS, 1)
fused_decode_kernel(const __grid_constant__ CUtensorMap tm_k, const __grid_constant__ CUtensorMap tm_v,
                    const __grid_constant__ CUtensorMap tm_vp,
                    const __grid_constant__ CUtensorMap tm_wq, const __grid_constant__ CUtensorMap tm_wo,
                    const __grid_constant__ CUtensorMap tm_wg, const __grid_constant__ CUtensorMap tm_wu,
                    const __grid_constant__ CUtensorMap tm_wd, const Params prm) {
    extern __shared__ uint8_t smem_raw[];
    const uint32_t sraw = smem_u32(smem_raw);
    const uint32_t sb = (sraw + 1023u) & ~1023u;
    uint8_t* sp = smem_raw + (sb - sraw);
    const int tid = threadIdx.x, warp = tid >> 5, lane = tid & 31;
    const int c = blockIdx.x;
    const bool is_ffn = c >= NATT;
    const uint32_t bar_full = sb + OFF_BAR, bar_empty = bar_full + NSTAGE * 8, bar_vp = bar_empty + NSTAGE * 8;

    TS(0);
    if (warp == NCW) {
        if (lane == 0) {
            for (int s = 0; s < NSTAGE; s++) {
                mbar_init(bar_full + s * 8, 1);
                mbar_init(bar_empty + s * 8, NCW);
            }
            for (int s = 0; s < NVP; s++) mbar_init(bar_vp + s * 8, 1);
            asm volatile("fence.mbarrier_init.release.cluster;" ::: "memory");
            asm volatile("fence.proxy.async.shared::cta;" ::: "memory");
        }
        const int nst = is_ffn ? FFN_STAGES : ATT_STAGES;
        const int kv_line0 = (((c >> 2) & 3) * kHKV + (c >> 4)) * (kSK * 2) + (c & 3) * (KEYS_PER_CTA * 2);
        const int f0 = (c - NATT) * FCOLS;
        uint64_t pol;
        asm volatile("createpolicy.fractional.L2::evict_first.b64 %0, 1.0;" : "=l"(pol));
        auto issue = [&](int i, int s) {
            const uint32_t bar = bar_full + s * 8, dst = sb + OFF_RING + s * STAGE;
            if (!is_ffn && i == 2 * NT) {
#pragma unroll 1
                for (int j = 0; j < NVP; j++) {
                    mbar_expect_tx(bar_vp + j * 8, STAGE / NVP);
                    tma2d_hint(dst + j * (STAGE / NVP), &tm_vp, 0, kv_line0 + (NT - 1) * 256 + j * (256 / NVP), bar_vp + j * 8, pol);
                }
                return;
            }
            mbar_expect_tx(bar, STAGE);
            if (!is_ffn) {
                if (i == 0) {
                    tma2d(dst, &tm_wq, 32 * c, 0, bar);
                    tma2d(dst + STAGE / 2, &tm_wq, 32 * c, 256, bar);
                } else if (i <= 2 * NT) {
                    const int t = (i - 1) >> 1;
                    tma2d_hint(dst, ((i - 1) & 1) ? &tm_v : &tm_k, 0, kv_line0 + t * 256, bar, pol);
                } else {
                    tma2d(dst, &tm_wo, 128 * (c & 3), 128 * (c >> 2), bar);
                    tma2d(dst + STAGE / 2, &tm_wo, 128 * (c & 3) + 64, 128 * (c >> 2), bar);
                }
            } else {
                if (i < 4 * FBLK) {
                    tma2d(dst, (i & 2) ? &tm_wu : &tm_wg, f0 + 64 * (i >> 2), 256 * (i & 1), bar);
                } else {
                    const int ii = i - 4 * FBLK;
#pragma unroll
                    for (int blk = 0; blk < 4; blk++)
                        tma2d(dst + blk * 8192, &tm_wd, 256 * (ii & 1) + 64 * blk, f0 + 64 * (ii >> 1), bar);
                }
            }
        };
        if (lane == 0) {
            TSP(16);
            for (int s = 0; s < WIN; s++) issue(s, s);
            TSP(17);
        }
        __syncthreads();
        if (lane == 0) {
            int s = WIN % NSTAGE, sw = 0;
            uint32_t ph = WIN == NSTAGE ? 0 : 1, phw = 0;
            const uint32_t ep = *reinterpret_cast<volatile uint32_t*>(sp + OFF_MISC + 4);
            uint32_t* prog = g_prog + (ep & 1u) * 32;
            if (c == 0) st_rlx(g_prog + ((ep + 1u) & 1u) * 32, 0u);
            uint32_t r_old = 0;
            int dly = 0;
            for (int i = WIN; i < nst; i++) {
                mbar_wait(bar_full + sw * 8, phw);
                const uint32_t t0 = clock();
                if (!is_ffn && (i & 1)) {
                    if (i >= 5) dly = min(max((64 * (i - 3) - (int)r_old - 1 - (PACE_L0)) * PACE_K, 0), PACE_MAX);
                    asm volatile("atom.relaxed.gpu.global.add.u32 %0, [%1], 1;" : "=r"(r_old) : "l"(prog) : "memory");
                }
                if (i >= NSTAGE) mbar_wait(bar_empty + s * 8, ph);
                if (WO_AT >= 0 && !is_ffn && i == ATT_STAGES - 1) {
                    mbar_wait(bar_vp + (WO_AT < 0 ? 0 : WO_AT) * 8, 0);
                }
                while ((int)(clock() - t0) < dly) {}
                issue(i, s);
                if (++s == NSTAGE) { s = 0; ph ^= 1; }
                if (++sw == NSTAGE) { sw = 0; phw ^= 1; }
            }
            TSP(18);
        }
        return;
    }

    {
        const uint4 xv = __ldg(reinterpret_cast<const uint4*>(prm.x) + tid);
        *reinterpret_cast<uint4*>(sp + OFF_X + ((tid >> 6) * XP + (tid & 63) * 8) * 2) = xv;
    }
    float* misc_f = reinterpret_cast<float*>(sp + OFF_MISC);
    uint32_t* misc_u = reinterpret_cast<uint32_t*>(sp + OFF_MISC);
    if (tid == 0) {
        uint32_t e;
        asm volatile("ld.relaxed.gpu.global.u32 %0, [%1];" : "=r"(e) : "l"(&g_epoch) : "memory");
        misc_u[1] = e;
    }
    if (warp == NCW - 1 && !is_ffn) {
        const int bf = c >> 5;
        const uint4* xp = reinterpret_cast<const uint4*>(prm.x + bf * kD) + lane * 2;
        const uint4* gp = reinterpret_cast<const uint4*>(prm.gate_w) + lane * 2;
        float acc = 0.f;
#pragma unroll
        for (int u = 0; u < 2; u++) {
            const uint4 a = __ldg(xp + u), g = __ldg(gp + u);
            const uint32_t aw[4] = {a.x, a.y, a.z, a.w}, gw[4] = {g.x, g.y, g.z, g.w};
#pragma unroll
            for (int e = 0; e < 4; e++) {
                acc = fmaf(__uint_as_float(aw[e] << 16), __uint_as_float(gw[e] << 16), acc);
                acc = fmaf(__uint_as_float(aw[e] & 0xffff0000u), __uint_as_float(gw[e] & 0xffff0000u), acc);
            }
        }
#pragma unroll
        for (int o = 16; o > 0; o >>= 1) acc += __shfl_xor_sync(0xffffffffu, acc, o);
        if (lane == 0) misc_f[0] = 1.f / (1.f + __expf(-acc));
    }
    __syncthreads();
    TS(1);
    const uint32_t epoch = misc_u[1];
    const uint32_t tag = (epoch + 1u) & 1u;

    const int r8 = lane & 7, mi = lane >> 3;
    const int rr = lane >> 2, jj = lane & 3;
    int st = 0;
    uint32_t ph = 0;
    auto advance = [&]() { if (++st == NSTAGE) { st = 0; ph ^= 1; } };
    auto release = [&]() {
        __syncwarp();
        if (lane == 0) mbar_arrive(bar_empty + st * 8);
        advance();
    };
    const uint32_t x_addr = sb + OFF_X + ((r8 & 3) * XP + mi * 8) * 2;

    if (is_ffn) {
        const int fi = c - NATT;
        if (lane < 16) {
            uint32_t* dst = g_pb + ((kHQ + fi) * kB + rr) * kD + (warp >> 1) * 64 + (warp & 1) * 32 + jj * 2;
#pragma unroll
            for (int ch = 0; ch < 2; ch++)
#pragma unroll
                for (int n = 0; n < 4; n++) st_rlx2(dst + ch * 256 + n * 8, tag ^ 1u, tag ^ 1u);
        }
        for (int jb = 0; jb < FBLK; jb++) {
            float gu[2][2][4];
#pragma unroll
            for (int m = 0; m < 2; m++) {
#pragma unroll
                for (int e = 0; e < 4; e++) gu[m][0][e] = gu[m][1][e] = 0.f;
#pragma unroll
                for (int kh = 0; kh < 2; kh++) {
                    mbar_wait(bar_full + st * 8, ph);
                    const uint32_t wb = sb + OFF_RING + st * STAGE + lane * 128 + ((warp ^ r8) << 4);
#pragma unroll
                    for (int kk = 0; kk < 8; kk++) {
                        uint32_t b0, b1, b2, b3, a0, a1, a2, a3;
                        ldsm4t(wb + kk * 4096, b0, b1, b2, b3);
                        ldsm4(x_addr + (kh * 256 + kk * 32) * 2, a0, a1, a2, a3);
                        mma16816(gu[m][0], a0, 0u, a1, 0u, b0, b1);
                        mma16816(gu[m][1], a2, 0u, a3, 0u, b2, b3);
                    }
                    release();
                }
            }
            const float g0 = bf16_round(gu[0][0][0] + gu[0][1][0]), g1 = bf16_round(gu[0][0][1] + gu[0][1][1]);
            const float u0 = bf16_round(gu[1][0][0] + gu[1][1][0]), u1 = bf16_round(gu[1][0][1] + gu[1][1][1]);
            const float h0 = (g0 > 0.f ? g0 : 0.f) * u0, h1 = (g1 > 0.f ? g1 : 0.f) * u1;
            if (lane < 16)
                *reinterpret_cast<uint32_t*>(sp + OFF_H + (rr * HP + jb * 64 + warp * 8 + jj * 2) * 2) = pack_bf16(h0, h1);
        }
        bar_consumers();
        TS(10);
        float acc[2][4][4];
#pragma unroll
        for (int ch = 0; ch < 2; ch++)
#pragma unroll
            for (int n = 0; n < 4; n++)
#pragma unroll
                for (int e = 0; e < 4; e++) acc[ch][n][e] = 0.f;
        const uint32_t h_addr = sb + OFF_H + ((r8 & 3) * HP + mi * 8) * 2;
        for (int jb = 0; jb < FBLK; jb++) {
            uint32_t a[8];
            ldsm4(h_addr + (jb * 64) * 2, a[0], a[1], a[2], a[3]);
            ldsm4(h_addr + (jb * 64 + 32) * 2, a[4], a[5], a[6], a[7]);
#pragma unroll
            for (int ch = 0; ch < 2; ch++) {
                mbar_wait(bar_full + st * 8, ph);
                const uint32_t wb = sb + OFF_RING + st * STAGE + (warp >> 1) * 8192 + (lane & 15) * 128;
#pragma unroll
                for (int ks = 0; ks < 4; ks++) {
#pragma unroll
                    for (int np = 0; np < 2; np++) {
                        uint32_t b0, b1, b2, b3;
                        const int chunk = (warp & 1) * 4 + np * 2 + (lane >> 4);
                        ldsm4t(wb + ks * 2048 + ((chunk ^ r8) << 4), b0, b1, b2, b3);
                        mma16816(acc[ch][np * 2], a[ks * 2], 0u, a[ks * 2 + 1], 0u, b0, b1);
                        mma16816(acc[ch][np * 2 + 1], a[ks * 2], 0u, a[ks * 2 + 1], 0u, b2, b3);
                    }
                }
                release();
            }
        }
        if (lane < 16) {
            uint32_t* dst = g_pb + ((kHQ + fi) * kB + rr) * kD + (warp >> 1) * 64 + (warp & 1) * 32 + jj * 2;
#pragma unroll
            for (int ch = 0; ch < 2; ch++)
#pragma unroll
                for (int n = 0; n < 4; n++)
                    st_rlx2(dst + ch * 256 + n * 8, tagw(acc[ch][n][0], tag), tagw(acc[ch][n][1], tag));
        }
        TS(15);
        return;
    }

    float* comb = reinterpret_cast<float*>(sp + OFF_COMB);
    float* mx_s = reinterpret_cast<float*>(sp + OFF_MX);
    float* l_s = reinterpret_cast<float*>(sp + OFF_L);
    const int hkv = c >> 4, batch = (c >> 2) & 3;
    {
        const uint32_t nr = tag ^ 1u;
        if (tid < 128) st_rlx(g_q + (tid >> 5) * (kHQ * kDH) + 32 * c + (tid & 31), nr);
        st_rlx2(g_pa + (c * 4 + (rr & 3)) * kDH + (rr >> 2) * 64 + warp * 8 + jj * 2, nr, nr);
        if (tid < 16 && jj == 0) st_rlx2(g_ml + (c * 4 + rr) * 2, nr, nr);
        if (jj < 2) {
            uint32_t* d2 = g_pb + ((c >> 2) * kB + jj * 2) * kD + (c & 3) * 128 + warp * 16 + rr;
            st_rlx(d2, nr);
            st_rlx(d2 + kD, nr);
            st_rlx(d2 + 8, nr);
            st_rlx(d2 + kD + 8, nr);
        }
    }

    {
        float qc[4][4];
#pragma unroll
        for (int n = 0; n < 4; n++)
#pragma unroll
            for (int e = 0; e < 4; e++) qc[n][e] = 0.f;
        uint32_t a[8];
        ldsm4(x_addr + (warp * 64) * 2, a[0], a[1], a[2], a[3]);
        ldsm4(x_addr + (warp * 64 + 32) * 2, a[4], a[5], a[6], a[7]);
        mbar_wait(bar_full + st * 8, ph);
        TS(2);
#pragma unroll
        for (int ks = 0; ks < 4; ks++) {
            const int row = warp * 64 + ks * 16 + (lane & 15);
#pragma unroll
            for (int np = 0; np < 2; np++) {
                uint32_t b0, b1, b2, b3;
                const int chunk = np * 2 + (lane >> 4);
                ldsm4t(sb + OFF_RING + st * STAGE + row * 64 + ((chunk ^ ((row >> 1) & 3)) << 4), b0, b1, b2, b3);
                mma16816(qc[np * 2], a[ks * 2], 0u, a[ks * 2 + 1], 0u, b0, b1);
                mma16816(qc[np * 2 + 1], a[ks * 2], 0u, a[ks * 2 + 1], 0u, b2, b3);
            }
        }
        release();
        if (lane < 16) {
#pragma unroll
            for (int n = 0; n < 4; n++)
                *reinterpret_cast<float2*>(comb + warp * 128 + rr * 32 + n * 8 + jj * 2) = make_float2(qc[n][0], qc[n][1]);
        }
        bar_consumers();
        if (tid < 128) {
            float s = 0.f;
#pragma unroll
            for (int w = 0; w < NCW; w++) s += comb[w * 128 + tid];
            st_rlx(g_q + (tid >> 5) * (kHQ * kDH) + 32 * c + (tid & 31), tagw(s, tag));
            TS(3);
            const uint32_t* qsrc = g_q + batch * (kHQ * kDH) + hkv * 512 + tid * 4;
            uint4 v = ld_rlx4(qsrc);
            int it = 0;
            while (!tag_ok(v, tag)) {
                if (++it > (1 << 21)) __trap();
                __nanosleep(64);
                v = ld_rlx4(qsrc);
            }
            uint2 pk;
            pk.x = pack_bf16(__uint_as_float(v.x), __uint_as_float(v.y));
            pk.y = pack_bf16(__uint_as_float(v.z), __uint_as_float(v.w));
            *reinterpret_cast<uint2*>(sp + OFF_Q + ((tid >> 5) * QP + (tid & 31) * 4) * 2) = pk;
        }
        bar_consumers();
    }
    TS(4);
    uint32_t qa[8];
    {
        const uint32_t qaddr = sb + OFF_Q + ((r8 & 3) * QP + (r8 >> 2) * 64 + mi * 8) * 2;
        ldsm4(qaddr, qa[0], qa[1], qa[2], qa[3]);
        ldsm4(qaddr + 64, qa[4], qa[5], qa[6], qa[7]);
    }

    float o[4][4];
#pragma unroll
    for (int m = 0; m < 4; m++)
#pragma unroll
        for (int e = 0; e < 4; e++) o[m][e] = 0.f;
    float m_run = -INFINITY, l_run = 0.f;
    const uint32_t k_off = (warp * 32 + r8) * 128 + ((mi ^ r8) << 4);
    const uint32_t v_off = (warp * 32 + (mi >> 1) * 8 + r8) * 128 + (((mi & 1) ^ r8) << 4);
    const uint32_t pmask = lane < 16 ? 0x0000ffffu : 0xffff0000u;
    float fsum[4] = {0.f, 0.f, 0.f, 0.f};
    const int bf = c >> 5, col_f = (c & 31) * 16 + (warp & 3) * 4;

    auto scores = [&](float (&sc)[4]) {
        float s[4][4];
        const uint32_t kb = sb + OFF_RING + st * STAGE;
#pragma unroll
        for (int g = 0; g < 4; g++) {
#pragma unroll
            for (int e = 0; e < 4; e++) s[g][e] = 0.f;
            uint32_t b0, b1, b2, b3;
            ldsm4(kb + k_off + g * 1024, b0, b1, b2, b3);
            mma16816(s[g], qa[0], 0u, qa[1], 0u, b0, b1);
            mma16816(s[g], qa[2], 0u, qa[3], 0u, b2, b3);
            ldsm4(kb + (k_off ^ 64u) + g * 1024, b0, b1, b2, b3);
            mma16816(s[g], qa[4], 0u, qa[5], 0u, b0, b1);
            mma16816(s[g], qa[6], 0u, qa[7], 0u, b2, b3);
        }
        release();
#pragma unroll
        for (int g = 0; g < 4; g++) {
            const float v = lane < 16 ? s[g][0] : s[g][1];
            sc[g] = v + __shfl_xor_sync(0xffffffffu, v, 16);
        }
    };
    auto rescale = [&](float m_new) {
        const float alpha = ex2((m_run - m_new) * kScaleLog2);
        l_run *= alpha;
        const float a0 = __shfl_sync(0xffffffffu, alpha, ((2 * jj) & 3) * 4);
        const float a1 = __shfl_sync(0xffffffffu, alpha, ((2 * jj + 1) & 3) * 4);
#pragma unroll
        for (int m = 0; m < 4; m++) {
            o[m][0] *= a0; o[m][1] *= a1; o[m][2] *= a0; o[m][3] *= a1;
        }
        m_run = m_new;
    };
    auto probs = [&](const float (&sc)[4], uint32_t (&pb)[4]) {
        const float mc = m_run * kScaleLog2;
#pragma unroll
        for (int g = 0; g < 4; g++) {
            const float p = ex2(fmaf(sc[g], kScaleLog2, -mc));
            l_run += p;
            pb[g] = pack_bf16(p, p) & pmask;
        }
    };

    for (int t = 0; t < NT - 1; t++) {
        mbar_wait(bar_full + st * 8, ph);
        float sc[4];
        scores(sc);
        float mx = fmaxf(fmaxf(sc[0], sc[1]), fmaxf(sc[2], sc[3]));
        mx = fmaxf(mx, __shfl_xor_sync(0xffffffffu, mx, 1));
        mx = fmaxf(mx, __shfl_xor_sync(0xffffffffu, mx, 2));
        const float m_new = fmaxf(m_run, mx);
        if (__any_sync(0xffffffffu, m_new > m_run)) rescale(m_new);
        uint32_t pb[4];
        probs(sc, pb);
        if (t == NT - 4 && warp < 4) {
            uint4 v = make_uint4(0, 0, 0, 0);
            if (lane < NFFN) v = poll4(g_pb + ((kHQ + lane) * kB + bf) * kD + col_f, tag);
            __syncwarp();
            fsum[0] = __uint_as_float(v.x); fsum[1] = __uint_as_float(v.y);
            fsum[2] = __uint_as_float(v.z); fsum[3] = __uint_as_float(v.w);
#pragma unroll
            for (int e = 0; e < 4; e++) {
                fsum[e] += __shfl_xor_sync(0xffffffffu, fsum[e], 1);
                fsum[e] += __shfl_xor_sync(0xffffffffu, fsum[e], 2);
            }
        }
        mbar_wait(bar_full + st * 8, ph);
        {
            const uint32_t vb = sb + OFF_RING + st * STAGE;
#pragma unroll
            for (int oc = 0; oc < 2; oc++) {
#pragma unroll
                for (int m = 0; m < 4; m++) {
                    uint32_t a0, a1, a2, a3;
                    ldsm4t(vb + ((v_off + oc * 2048) ^ (m * 32)), a0, a1, a2, a3);
                    mma16816(o[m], a0, a1, a2, a3, pb[oc * 2], pb[oc * 2 + 1]);
                }
            }
        }
        release();
    }

    {
        mbar_wait(bar_full + st * 8, ph);
        TS(9);
        float sc[4];
        scores(sc);
        float mx = fmaxf(fmaxf(sc[0], sc[1]), fmaxf(sc[2], sc[3]));
        mx = fmaxf(mx, __shfl_xor_sync(0xffffffffu, mx, 1));
        mx = fmaxf(mx, __shfl_xor_sync(0xffffffffu, mx, 2));
        float m_new = fmaxf(m_run, mx);
        if (lane < 16 && jj == 0) mx_s[warp * 4 + rr] = m_new;
        bar_consumers();
#pragma unroll
        for (int w = 0; w < NCW; w++) m_new = fmaxf(m_new, mx_s[w * 4 + (rr & 3)]);
        if (__any_sync(0xffffffffu, m_new > m_run)) rescale(m_new);
        uint32_t pb[4];
        probs(sc, pb);
        l_run += __shfl_xor_sync(0xffffffffu, l_run, 1);
        l_run += __shfl_xor_sync(0xffffffffu, l_run, 2);
        if (lane < 16 && jj == 0) l_s[warp * 4 + rr] = l_run;
        uint4* pbuf = reinterpret_cast<uint4*>(sp + OFF_X);
        pbuf[tid] = make_uint4(pb[0], pb[1], pb[2], pb[3]);
        {
            float* dst = comb + warp * COMB_W + jj * 8 + rr;
#pragma unroll
            for (int m = 0; m < 4; m++)
#pragma unroll
                for (int e = 0; e < 4; e++) dst[(2 * m + (e >> 1)) * 80 + (e & 1) * 48] = o[m][e];
        }
        bar_consumers();
        if (tid < 16 && jj == 0) {
            float l = 0.f;
#pragma unroll
            for (int w = 0; w < NCW; w++) l += l_s[w * 4 + rr];
            st_rlx2(g_ml + (c * 4 + rr) * 2, tagw(m_run, tag), tagw(l, tag));
        }
        float2 prev;
        {
            const float* src = comb + warp * 80 + (rr & 1) * 48 + (rr >> 1) * 8 + jj * 2;
            prev = *reinterpret_cast<const float2*>(src);
#pragma unroll
            for (int w = 1; w < NCW; w++) {
                const float2 v = *reinterpret_cast<const float2*>(src + w * COMB_W);
                prev.x += v.x; prev.y += v.y;
            }
        }
        uint4 pf[NVP];
#pragma unroll
        for (int j = 0; j < NVP; j++) pf[j] = pbuf[j * 32 + lane];
        float acc[4][4];
#pragma unroll
        for (int u = 0; u < 4; u++)
#pragma unroll
            for (int e = 0; e < 4; e++) acc[u][e] = 0.f;
        acc[0][0] = prev.x; acc[0][1] = prev.y;
        const uint32_t vb = sb + OFF_RING + st * STAGE + lane * 128 + ((warp ^ r8) << 4);
#pragma unroll
        for (int j = 0; j < NVP; j++) {
            mbar_wait(bar_vp + j * 8, 0);
            uint32_t b0, b1, b2, b3;
            ldsm4t(vb + j * (STAGE / NVP), b0, b1, b2, b3);
            mma16816(acc[(j & 1) * 2], pf[j].x, 0u, pf[j].y, 0u, b0, b1);
            mma16816(acc[(j & 1) * 2 + 1], pf[j].z, 0u, pf[j].w, 0u, b2, b3);
        }
        TS(10);
        advance();
        st_rlx2(g_pa + (c * 4 + (rr & 3)) * kDH + (rr >> 2) * 64 + warp * 8 + jj * 2,
                tagw((acc[0][0] + acc[1][0]) + (acc[2][0] + acc[3][0]), tag),
                tagw((acc[0][1] + acc[1][1]) + (acc[2][1] + acc[3][1]), tag));
    }
    TS(11);

    uint32_t wf[8][4];
    auto load_wo = [&]() {
        mbar_wait(bar_full + st * 8, ph);
        TS(20);
        const uint32_t wb = sb + OFF_RING + st * STAGE + (warp >> 2) * 16384 + ((mi >> 1) * 8 + r8) * 128 +
                            ((((warp & 3) * 2 + (mi & 1)) ^ r8) << 4);
#pragma unroll
        for (int ks = 0; ks < 8; ks++) ldsm4t(wb + ks * 2048, wf[ks][0], wf[ks][1], wf[ks][2], wf[ks][3]);
    };
    {
        const int hh = (c >> 2) & 3;
        const uint32_t* pm = g_ml + (((c & ~15) | ((warp >> 1) << 2)) * 4 + hh) * 2;
        const uint32_t* po = g_pa + (((c & ~15) | ((warp >> 1) << 2)) * 4 + hh) * kDH + (warp & 1) * 64 + lane * 2;
        uint2 v[4];
        auto load_pa = [&](uint2 (&d)[4]) {
#pragma unroll
            for (int s = 0; s < 4; s++) d[s] = ld_rlx2(po + s * (4 * kDH));
        };
        auto pa_ok = [&](const uint2 (&d)[4]) {
            return ((((d[0].x ^ tag) | (d[0].y ^ tag) | (d[1].x ^ tag) | (d[1].y ^ tag) | (d[2].x ^ tag) | (d[2].y ^ tag) |
                      (d[3].x ^ tag) | (d[3].y ^ tag)) & 1u) == 0);
        };
        uint2 mlv[4];
#pragma unroll
        for (int s = 0; s < 4; s++) mlv[s] = ld_rlx2(pm + s * 8);
        int it = 0;
        while (!pa_ok(mlv)) {
            if (++it > (1 << 21)) __trap();
#pragma unroll
            for (int s = 0; s < 4; s++) mlv[s] = ld_rlx2(pm + s * 8);
        }
        TS(19);
        float w4[4];
        {
            const float ms[4] = {__uint_as_float(mlv[0].x), __uint_as_float(mlv[1].x), __uint_as_float(mlv[2].x), __uint_as_float(mlv[3].x)};
            const float ls[4] = {__uint_as_float(mlv[0].y), __uint_as_float(mlv[1].y), __uint_as_float(mlv[2].y), __uint_as_float(mlv[3].y)};
            const float M = fmaxf(fmaxf(ms[0], ms[1]), fmaxf(ms[2], ms[3]));
            float L = 0.f;
#pragma unroll
            for (int s = 0; s < 4; s++) {
                w4[s] = ex2((ms[s] - M) * kScaleLog2);
                L = fmaf(w4[s], ls[s], L);
            }
            const float inv = 1.f / L;
#pragma unroll
            for (int s = 0; s < 4; s++) w4[s] *= inv;
        }
        load_wo();
        load_pa(v);
        if (!__all_sync(0xffffffffu, pa_ok(v))) {
            do {
                if (++it > (1 << 21)) __trap();
                load_pa(v);
            } while (!__all_sync(0xffffffffu, pa_ok(v)));
        }
        TS(12);
        float z0 = 0.f, z1 = 0.f;
#pragma unroll
        for (int s = 0; s < 4; s++) {
            z0 = fmaf(w4[s], __uint_as_float(v[s].x), z0);
            z1 = fmaf(w4[s], __uint_as_float(v[s].y), z1);
        }
        *reinterpret_cast<uint32_t*>(sp + OFF_Q + ((warp >> 1) * QP + (warp & 1) * 64 + lane * 2) * 2) = pack_bf16(z0, z1);
    }
    bar_consumers();
    {
        const uint32_t oaddr = sb + OFF_Q + ((r8 & 3) * QP + mi * 8) * 2;
        float acc[4][4];
#pragma unroll
        for (int u = 0; u < 4; u++)
#pragma unroll
            for (int e = 0; e < 4; e++) acc[u][e] = 0.f;
#pragma unroll
        for (int kp = 0; kp < 4; kp++) {
            uint32_t b0, b1, b2, b3;
            ldsm4(oaddr + kp * 64, b0, b1, b2, b3);
            mma16816(acc[(kp & 1) * 2], wf[kp * 2][0], wf[kp * 2][1], wf[kp * 2][2], wf[kp * 2][3], b0, b1);
            mma16816(acc[(kp & 1) * 2 + 1], wf[kp * 2 + 1][0], wf[kp * 2 + 1][1], wf[kp * 2 + 1][2], wf[kp * 2 + 1][3], b2, b3);
        }
        if (jj < 2) {
            uint32_t* dst = g_pb + ((c >> 2) * kB + jj * 2) * kD + (c & 3) * 128 + warp * 16 + rr;
            st_rlx(dst, tagw((acc[0][0] + acc[1][0]) + (acc[2][0] + acc[3][0]), tag));
            st_rlx(dst + kD, tagw((acc[0][1] + acc[1][1]) + (acc[2][1] + acc[3][1]), tag));
            st_rlx(dst + 8, tagw((acc[0][2] + acc[1][2]) + (acc[2][2] + acc[3][2]), tag));
            st_rlx(dst + kD + 8, tagw((acc[0][3] + acc[1][3]) + (acc[2][3] + acc[3][3]), tag));
        }
    }
    TS(13);
    if (warp < 4) {
        const uint32_t* pbp = g_pb + (lane * kB + bf) * kD + col_f;
        const uint4 v = poll4(pbp, tag);
        __syncwarp();
        TS(14);
        float a[4] = {__uint_as_float(v.x), __uint_as_float(v.y), __uint_as_float(v.z), __uint_as_float(v.w)};
#pragma unroll
        for (int ofs = 16; ofs > 0; ofs >>= 1)
#pragma unroll
            for (int e = 0; e < 4; e++) a[e] += __shfl_xor_sync(0xffffffffu, a[e], ofs);
        if (lane == 0) {
            const float g = misc_f[0];
            uint2 pk;
            pk.x = pack_bf16(g * a[0] + (1.f - g) * fsum[0], g * a[1] + (1.f - g) * fsum[1]);
            pk.y = pack_bf16(g * a[2] + (1.f - g) * fsum[2], g * a[3] + (1.f - g) * fsum[3]);
            *reinterpret_cast<uint2*>(prm.out + bf * kD + col_f) = pk;
            TS(15);
            if (c == 0 && warp == 0) {
                asm volatile("st.relaxed.gpu.global.u32 [%0], %1;" ::"l"(&g_epoch), "r"(epoch + 1u) : "memory");
            }
        }
    }
}

typedef CUresult (*EncodeFn)(CUtensorMap*, CUtensorMapDataType, cuuint32_t, void*, const cuuint64_t*, const cuuint64_t*,
                             const cuuint32_t*, const cuuint32_t*, CUtensorMapInterleave, CUtensorMapSwizzle,
                             CUtensorMapL2promotion, CUtensorMapFloatOOBfill);

void encode2d(EncodeFn enc, CUtensorMap* m, const void* base, uint64_t cols, uint64_t rows, uint64_t pitch_bytes,
              uint32_t box_cols, uint32_t box_rows, CUtensorMapSwizzle swz) {
    cuuint64_t gd[2] = {cols, rows};
    cuuint64_t gs[1] = {pitch_bytes};
    cuuint32_t bd[2] = {box_cols, box_rows};
    cuuint32_t es[2] = {1, 1};
    enc(m, CU_TENSOR_MAP_DATA_TYPE_BFLOAT16, 2, const_cast<void*>(base), gd, gs, bd, es, CU_TENSOR_MAP_INTERLEAVE_NONE,
        swz, CU_TENSOR_MAP_L2_PROMOTION_L2_128B, CU_TENSOR_MAP_FLOAT_OOB_FILL_NONE);
}

}

extern "C" void kernel_launch(void* const* d_in, const int* in_sizes, int n_in, void* d_out, int out_size) {
    (void)in_sizes; (void)n_in; (void)out_size;
    static EncodeFn enc = nullptr;
    if (!enc) {
        void* fn = nullptr;
        cudaDriverEntryPointQueryResult qr;
        cudaGetDriverEntryPoint("cuTensorMapEncodeTiled", &fn, cudaEnableDefault, &qr);
        enc = reinterpret_cast<EncodeFn>(fn);
        cudaFuncSetAttribute(fused_decode_kernel, cudaFuncAttributeMaxDynamicSharedMemorySize, SMEM_BYTES);
    }
    CUtensorMap tk, tv, tvp, twq, two, twg, twu, twd;
    encode2d(enc, &tk, d_in[1], 64, (uint64_t)kB * kHKV * kSK * 2, 128, 64, 256, CU_TENSOR_MAP_SWIZZLE_128B);
    encode2d(enc, &tv, d_in[2], 64, (uint64_t)kB * kHKV * kSK * 2, 128, 64, 256, CU_TENSOR_MAP_SWIZZLE_128B);
    encode2d(enc, &tvp, d_in[2], 64, (uint64_t)kB * kHKV * kSK * 2, 128, 64, 256 / NVP, CU_TENSOR_MAP_SWIZZLE_128B);
    encode2d(enc, &twq, d_in[3], kHQ * kDH, kD, kHQ * kDH * 2, 32, 256, CU_TENSOR_MAP_SWIZZLE_64B);
    encode2d(enc, &two, d_in[4], kD, kHQ * kDH, kD * 2, 64, 128, CU_TENSOR_MAP_SWIZZLE_128B);
    encode2d(enc, &twg, d_in[6], kF, kD, kF * 2, 64, 256, CU_TENSOR_MAP_SWIZZLE_128B);
    encode2d(enc, &twu, d_in[7], kF, kD, kF * 2, 64, 256, CU_TENSOR_MAP_SWIZZLE_128B);
    encode2d(enc, &twd, d_in[8], kD, kF, kD * 2, 64, 64, CU_TENSOR_MAP_SWIZZLE_128B);
    Params prm;
    prm.x = reinterpret_cast<const __nv_bfloat16*>(d_in[0]);
    prm.gate_w = reinterpret_cast<const __nv_bfloat16*>(d_in[9]);
    prm.out = reinterpret_cast<__nv_bfloat16*>(d_out);
    fused_decode_kernel<<<NCTA, NTHREADS, SMEM_BYTES>>>(tk, tv, tvp, twq, two, twg, twu, twd, prm);
}
```

```cpp
#include <cuda_runtime.h>
#include <cuda_bf16.h>
#include <cuda.h>
#include <stdint.h>

#define EVICT_FIRST 1
#define WIN 2
#define INIT_WRITES 1
#define PACE 1
#define PACE_K 16
#define PACE_L0 (-32)
#define PACE_MAX 2000
#define WO_AT 7
#define DLY_M 650
#define DLY_B 250

namespace {

constexpr int kB = 4, kD = 512, kHQ = 32, kHKV = 8, kDH = 128, kSK = 16384, kF = 1792;
constexpr int NATT = 128;
constexpr int NFFN = 4;
constexpr int NCTA = NATT + NFFN;
constexpr int NSTAGE = 6;
constexpr int STAGE = 32768;
constexpr int NCW = 8;
constexpr int NTHREADS = (NCW + 1) * 32;
constexpr int KEYS_PER_CTA = kSK / 4;
constexpr int NT = KEYS_PER_CTA / 128;
constexpr int ATT_STAGES = 2 + 2 * NT;
constexpr int FCOLS = kF / NFFN;
constexpr int FBLK = FCOLS / 64;
constexpr int FFN_STAGES = 4 * FBLK + 2 * FBLK;

constexpr int XP = 520;
constexpr int QP = 136;
constexpr int HP = FCOLS + 8;
constexpr int COMB_W = 640;
constexpr int OFF_RING = 0;
constexpr int OFF_COMB = NSTAGE * STAGE;
constexpr int OFF_X = OFF_COMB + NCW * COMB_W * 4;
constexpr int OFF_Q = OFF_X + kB * XP * 2;
constexpr int OFF_H = OFF_Q + kB * QP * 2;
constexpr int OFF_MX = OFF_H + kB * HP * 2;
constexpr int OFF_L = OFF_MX + NCW * 4 * 4;
constexpr int OFF_MISC = OFF_L + NCW * 4 * 4;
constexpr int OFF_BAR = OFF_MISC + 16;
constexpr int NVP = 8;
constexpr int SMEM_USED = OFF_BAR + (2 * NSTAGE + NVP) * 8;
constexpr int SMEM_BYTES = SMEM_USED + 1024;
static_assert(SMEM_BYTES <= 232448, "smem");
static_assert(OFF_X % 16 == 0 && OFF_Q % 16 == 0 && OFF_H % 16 == 0 && OFF_BAR % 8 == 0, "align");

constexpr float kScaleLog2 = 0.08838834764831845f * 1.4426950408889634f;

__device__ uint32_t g_epoch;
__device__ __align__(128) uint32_t g_prog[2 * 32];
__device__ __align__(128) uint32_t g_q[kB * kHQ * kDH];
__device__ __align__(128) uint32_t g_pa[NATT * 4 * kDH];
__device__ __align__(128) uint32_t g_ml[NATT * 4 * 2];
__device__ __align__(128) uint32_t g_pb[(kHQ + NFFN) * kB * kD];

#define TS(i)
#define TSP(i)

__device__ __forceinline__ uint32_t smem_u32(const void* p) { return (uint32_t)__cvta_generic_to_shared(p); }
__device__ __forceinline__ void mbar_init(uint32_t bar, uint32_t cnt) {
    asm volatile("mbarrier.init.shared::cta.b64 [%0], %1;" ::"r"(bar), "r"(cnt));
}
__device__ __forceinline__ void mbar_expect_tx(uint32_t bar, uint32_t bytes) {
    asm volatile("mbarrier.arrive.expect_tx.shared::cta.b64 _, [%0], %1;" ::"r"(bar), "r"(bytes) : "memory");
}
__device__ __forceinline__ void mbar_arrive(uint32_t bar) {
    asm volatile("mbarrier.arrive.shared::cta.b64 _, [%0];" ::"r"(bar) : "memory");
}
__device__ __forceinline__ bool mbar_try_wait(uint32_t bar, uint32_t parity) {
    uint32_t ok;
    asm volatile("{\n.reg .pred p;\nmbarrier.try_wait.parity.shared::cta.b64 p, [%1], %2;\nselp.u32 %0, 1, 0, p;\n}"
                 : "=r"(ok) : "r"(bar), "r"(parity) : "memory");
    return ok;
}
__device__ __forceinline__ void mbar_wait(uint32_t bar, uint32_t parity) {
    if (mbar_try_wait(bar, parity)) return;
    const long long t0 = clock64();
    while (!mbar_try_wait(bar, parity)) {
        if (clock64() - t0 > 4000000000LL) __trap();
    }
}
__device__ __forceinline__ void tma2d(uint32_t dst, const CUtensorMap* m, int c0, int c1, uint32_t bar) {
    asm volatile("cp.async.bulk.tensor.2d.shared::cluster.global.mbarrier::complete_tx::bytes [%0], [%1, {%3, %4}], [%2];"
                 ::"r"(dst), "l"(m), "r"(bar), "r"(c0), "r"(c1) : "memory");
}
__device__ __forceinline__ void tma2d_hint(uint32_t dst, const CUtensorMap* m, int c0, int c1, uint32_t bar, uint64_t pol) {
    asm volatile("cp.async.bulk.tensor.2d.shared::cluster.global.mbarrier::complete_tx::bytes.L2::cache_hint"
                 " [%0], [%1, {%3, %4}], [%2], %5;"
                 ::"r"(dst), "l"(m), "r"(bar), "r"(c0), "r"(c1), "l"(pol) : "memory");
}
__device__ __forceinline__ void prefetch_tmap(const CUtensorMap* m) {
    asm volatile("prefetch.tensormap [%0];" ::"l"(m) : "memory");
}
__device__ __forceinline__ void ldsm4(uint32_t addr, uint32_t& r0, uint32_t& r1, uint32_t& r2, uint32_t& r3) {
    asm volatile("ldmatrix.sync.aligned.m8n8.x4.shared.b16 {%0,%1,%2,%3}, [%4];"
                 : "=r"(r0), "=r"(r1), "=r"(r2), "=r"(r3) : "r"(addr) : "memory");
}
__device__ __forceinline__ void ldsm4t(uint32_t addr, uint32_t& r0, uint32_t& r1, uint32_t& r2, uint32_t& r3) {
    asm volatile("ldmatrix.sync.aligned.m8n8.x4.trans.shared.b16 {%0,%1,%2,%3}, [%4];"
                 : "=r"(r0), "=r"(r1), "=r"(r2), "=r"(r3) : "r"(addr) : "memory");
}
__device__ __forceinline__ void mma16816(float (&c)[4], uint32_t a0, uint32_t a1, uint32_t a2, uint32_t a3,
                                         uint32_t b0, uint32_t b1) {
    asm volatile("mma.sync.aligned.m16n8k16.row.col.f32.bf16.bf16.f32 {%0,%1,%2,%3}, {%4,%5,%6,%7}, {%8,%9}, {%0,%1,%2,%3};"
                 : "+f"(c[0]), "+f"(c[1]), "+f"(c[2]), "+f"(c[3])
                 : "r"(a0), "r"(a1), "r"(a2), "r"(a3), "r"(b0), "r"(b1));
}
__device__ __forceinline__ float ex2(float x) {
    float y;
    asm("ex2.approx.ftz.f32 %0, %1;" : "=f"(y) : "f"(x));
    return y;
}
__device__ __forceinline__ uint32_t pack_bf16(float lo, float hi) {
    uint32_t r;
    asm("cvt.rn.bf16x2.f32 %0, %1, %2;" : "=r"(r) : "f"(hi), "f"(lo));
    return r;
}
__device__ __forceinline__ float bf16_round(float v) { return __bfloat162float(__float2bfloat16_rn(v)); }
__device__ __forceinline__ void spin(int cycles) {
    const uint32_t t0 = clock();
    while ((int)(clock() - t0) < cycles) {}
}
__device__ __forceinline__ void bar_consumers() { asm volatile("bar.sync 1, 256;" ::: "memory"); }

__device__ __forceinline__ uint32_t tagw(float v, uint32_t tag) { return (__float_as_uint(v) & ~1u) | tag; }
__device__ __forceinline__ void st_rlx(uint32_t* p, uint32_t v) {
    asm volatile("st.relaxed.gpu.global.u32 [%0], %1;" ::"l"(p), "r"(v) : "memory");
}
__device__ __forceinline__ void st_rlx2(uint32_t* p, uint32_t a, uint32_t b) {
    asm volatile("st.relaxed.gpu.global.v2.u32 [%0], {%1,%2};" ::"l"(p), "r"(a), "r"(b) : "memory");
}
__device__ __forceinline__ uint4 ld_rlx4(const uint32_t* p) {
    uint4 v;
    asm volatile("ld.relaxed.gpu.global.v4.u32 {%0,%1,%2,%3}, [%4];"
                 : "=r"(v.x), "=r"(v.y), "=r"(v.z), "=r"(v.w) : "l"(p) : "memory");
    return v;
}
__device__ __forceinline__ uint2 ld_rlx2(const uint32_t* p) {
    uint2 v;
    asm volatile("ld.relaxed.gpu.global.v2.u32 {%0,%1}, [%2];" : "=r"(v.x), "=r"(v.y) : "l"(p) : "memory");
    return v;
}
__device__ __forceinline__ bool tag_ok(uint4 v, uint32_t tag) {
    return (((v.x ^ tag) | (v.y ^ tag) | (v.z ^ tag) | (v.w ^ tag)) & 1u) == 0;
}
__device__ __forceinline__ uint4 poll4(const uint32_t* p, uint32_t tag) {
    uint4 v = ld_rlx4(p);
    int it = 0;
    while (!tag_ok(v, tag)) {
        if (++it > (1 << 21)) __trap();
        v = ld_rlx4(p);
    }
    return v;
}

struct Params {
    const __nv_bfloat16* x;
    const __nv_bfloat16* gate_w;
    __nv_bfloat16* out;
};

__global__ void __launch_bounds__(NTHREADS, 1)
fused_decode_kernel(const __grid_constant__ CUtensorMap tm_k, const __grid_constant__ CUtensorMap tm_v,
                    const __grid_constant__ CUtensorMap tm_vp,
                    const __grid_constant__ CUtensorMap tm_wq, const __grid_constant__ CUtensorMap tm_wo,
                    const __grid_constant__ CUtensorMap tm_wg, const __grid_constant__ CUtensorMap tm_wu,
                    const __grid_constant__ CUtensorMap tm_wd, const Params prm) {
    extern __shared__ uint8_t smem_raw[];
    const uint32_t sraw = smem_u32(smem_raw);
    const uint32_t sb = (sraw + 1023u) & ~1023u;
    uint8_t* sp = smem_raw + (sb - sraw);
    const int tid = threadIdx.x, warp = tid >> 5, lane = tid & 31;
    const int c = blockIdx.x;
    const bool is_ffn = c >= NATT;
    const uint32_t bar_full = sb + OFF_BAR, bar_empty = bar_full + NSTAGE * 8, bar_vp = bar_empty + NSTAGE * 8;

    TS(0);
    if (warp == NCW) {
        if (lane == 0) {
            for (int s = 0; s < NSTAGE; s++) {
                mbar_init(bar_full + s * 8, 1);
                mbar_init(bar_empty + s * 8, NCW);
            }
            for (int s = 0; s < NVP; s++) mbar_init(bar_vp + s * 8, 1);
            asm volatile("fence.mbarrier_init.release.cluster;" ::: "memory");
            asm volatile("fence.proxy.async.shared::cta;" ::: "memory");
        }
        const int nst = is_ffn ? FFN_STAGES : ATT_STAGES;
        const int kv_line0 = (((c >> 2) & 3) * kHKV + (c >> 4)) * (kSK * 2) + (c & 3) * (KEYS_PER_CTA * 2);
        const int f0 = (c - NATT) * FCOLS;
        uint64_t pol;
        asm volatile("createpolicy.fractional.L2::evict_first.b64 %0, 1.0;" : "=l"(pol));
        auto issue = [&](int i, int s) {
            const uint32_t bar = bar_full + s * 8, dst = sb + OFF_RING + s * STAGE;
            if (!is_ffn && i == 2 * NT) {
#pragma unroll 1
                for (int j = 0; j < NVP; j++) {
                    mbar_expect_tx(bar_vp + j * 8, STAGE / NVP);
                    tma2d_hint(dst + j * (STAGE / NVP), &tm_vp, 0, kv_line0 + (NT - 1) * 256 + j * (256 / NVP), bar_vp + j * 8, pol);
                }
                return;
            }
            mbar_expect_tx(bar, STAGE);
            if (!is_ffn) {
                if (i == 0) {
                    tma2d(dst, &tm_wq, 32 * c, 0, bar);
                    tma2d(dst + STAGE / 2, &tm_wq, 32 * c, 256, bar);
                } else if (i <= 2 * NT) {
                    const int t = (i - 1) >> 1;
                    tma2d_hint(dst, ((i - 1) & 1) ? &tm_v : &tm_k, 0, kv_line0 + t * 256, bar, pol);
                } else {
                    tma2d(dst, &tm_wo, 128 * (c & 3), 128 * (c >> 2), bar);
                    tma2d(dst + STAGE / 2, &tm_wo, 128 * (c & 3) + 64, 128 * (c >> 2), bar);
                }
            } else {
                if (i < 4 * FBLK) {
                    tma2d(dst, (i & 2) ? &tm_wu : &tm_wg, f0 + 64 * (i >> 2), 256 * (i & 1), bar);
                } else {
                    const int ii = i - 4 * FBLK;
#pragma unroll
                    for (int blk = 0; blk < 4; blk++)
                        tma2d(dst + blk * 8192, &tm_wd, 256 * (ii & 1) + 64 * blk, f0 + 64 * (ii >> 1), bar);
                }
            }
        };
        if (lane == 0) {
            TSP(16);
            for (int s = 0; s < WIN; s++) issue(s, s);
            TSP(17);
        }
        __syncthreads();
        if (lane == 0) {
            int s = WIN % NSTAGE, sw = 0;
            uint32_t ph = WIN == NSTAGE ? 0 : 1, phw = 0;
            const uint32_t ep = *reinterpret_cast<volatile uint32_t*>(sp + OFF_MISC + 4);
            uint32_t* prog = g_prog + (ep & 1u) * 32;
            if (c == 0) st_rlx(g_prog + ((ep + 1u) & 1u) * 32, 0u);
            uint32_t r_old = 0;
            int dly = 0;
            for (int i = WIN; i < nst; i++) {
                mbar_wait(bar_full + sw * 8, phw);
                const uint32_t t0 = clock();
                if (!is_ffn && (i & 1)) {
                    if (i >= 5) dly = min(max((64 * (i - 3) - (int)r_old - 1 - (PACE_L0)) * PACE_K, 0), PACE_MAX);
                    asm volatile("atom.relaxed.gpu.global.add.u32 %0, [%1], 1;" : "=r"(r_old) : "l"(prog) : "memory");
                }
                if (i >= NSTAGE) mbar_wait(bar_empty + s * 8, ph);
                if (WO_AT >= 0 && !is_ffn && i == ATT_STAGES - 1) {
                    mbar_wait(bar_vp + (WO_AT < 0 ? 0 : WO_AT) * 8, 0);
                }
                while ((int)(clock() - t0) < dly) {}
                issue(i, s);
                if (++s == NSTAGE) { s = 0; ph ^= 1; }
                if (++sw == NSTAGE) { sw = 0; phw ^= 1; }
            }
            TSP(18);
        }
        return;
    }

    {
        const uint4 xv = __ldg(reinterpret_cast<const uint4*>(prm.x) + tid);
        *reinterpret_cast<uint4*>(sp + OFF_X + ((tid >> 6) * XP + (tid & 63) * 8) * 2) = xv;
    }
    float* misc_f = reinterpret_cast<float*>(sp + OFF_MISC);
    uint32_t* misc_u = reinterpret_cast<uint32_t*>(sp + OFF_MISC);
    if (tid == 0) {
        uint32_t e;
        asm volatile("ld.relaxed.gpu.global.u32 %0, [%1];" : "=r"(e) : "l"(&g_epoch) : "memory");
        misc_u[1] = e;
    }
    if (warp == NCW - 1 && !is_ffn) {
        const int bf = c >> 5;
        const uint4* xp = reinterpret_cast<const uint4*>(prm.x + bf * kD) + lane * 2;
        const uint4* gp = reinterpret_cast<const uint4*>(prm.gate_w) + lane * 2;
        float acc = 0.f;
#pragma unroll
        for (int u = 0; u < 2; u++) {
            const uint4 a = __ldg(xp + u), g = __ldg(gp + u);
            const uint32_t aw[4] = {a.x, a.y, a.z, a.w}, gw[4] = {g.x, g.y, g.z, g.w};
#pragma unroll
            for (int e = 0; e < 4; e++) {
                acc = fmaf(__uint_as_float(aw[e] << 16), __uint_as_float(gw[e] << 16), acc);
                acc = fmaf(__uint_as_float(aw[e] & 0xffff0000u), __uint_as_float(gw[e] & 0xffff0000u), acc);
            }
        }
#pragma unroll
        for (int o = 16; o > 0; o >>= 1) acc += __shfl_xor_sync(0xffffffffu, acc, o);
        if (lane == 0) misc_f[0] = 1.f / (1.f + __expf(-acc));
    }
    __syncthreads();
    TS(1);
    const uint32_t epoch = misc_u[1];
    const uint32_t tag = (epoch + 1u) & 1u;

    const int r8 = lane & 7, mi = lane >> 3;
    const int rr = lane >> 2, jj = lane & 3;
    int st = 0;
    uint32_t ph = 0;
    auto advance = [&]() { if (++st == NSTAGE) { st = 0; ph ^= 1; } };
    auto release = [&]() {
        __syncwarp();
        if (lane == 0) mbar_arrive(bar_empty + st * 8);
        advance();
    };
    const uint32_t x_addr = sb + OFF_X + ((r8 & 3) * XP + mi * 8) * 2;

    if (is_ffn) {
        const int fi = c - NATT;
        if (lane < 16) {
            uint32_t* dst = g_pb + ((kHQ + fi) * kB + rr) * kD + (warp >> 1) * 64 + (warp & 1) * 32 + jj * 2;
#pragma unroll
            for (int ch = 0; ch < 2; ch++)
#pragma unroll
                for (int n = 0; n < 4; n++) st_rlx2(dst + ch * 256 + n * 8, tag ^ 1u, tag ^ 1u);
        }
        for (int jb = 0; jb < FBLK; jb++) {
            float gu[2][2][4];
#pragma unroll
            for (int m = 0; m < 2; m++) {
#pragma unroll
                for (int e = 0; e < 4; e++) gu[m][0][e] = gu[m][1][e] = 0.f;
#pragma unroll
                for (int kh = 0; kh < 2; kh++) {
                    mbar_wait(bar_full + st * 8, ph);
                    const uint32_t wb = sb + OFF_RING + st * STAGE + lane * 128 + ((warp ^ r8) << 4);
#pragma unroll
                    for (int kk = 0; kk < 8; kk++) {
                        uint32_t b0, b1, b2, b3, a0, a1, a2, a3;
                        ldsm4t(wb + kk * 4096, b0, b1, b2, b3);
                        ldsm4(x_addr + (kh * 256 + kk * 32) * 2, a0, a1, a2, a3);
                        mma16816(gu[m][0], a0, 0u, a1, 0u, b0, b1);
                        mma16816(gu[m][1], a2, 0u, a3, 0u, b2, b3);
                    }
                    release();
                }
            }
            const float g0 = bf16_round(gu[0][0][0] + gu[0][1][0]), g1 = bf16_round(gu[0][0][1] + gu[0][1][1]);
            const float u0 = bf16_round(gu[1][0][0] + gu[1][1][0]), u1 = bf16_round(gu[1][0][1] + gu[1][1][1]);
            const float h0 = (g0 > 0.f ? g0 : 0.f) * u0, h1 = (g1 > 0.f ? g1 : 0.f) * u1;
            if (lane < 16)
                *reinterpret_cast<uint32_t*>(sp + OFF_H + (rr * HP + jb * 64 + warp * 8 + jj * 2) * 2) = pack_bf16(h0, h1);
        }
        bar_consumers();
        TS(10);
        float acc[2][4][4];
#pragma unroll
        for (int ch = 0; ch < 2; ch++)
#pragma unroll
            for (int n = 0; n < 4; n++)
#pragma unroll
                for (int e = 0; e < 4; e++) acc[ch][n][e] = 0.f;
        const uint32_t h_addr = sb + OFF_H + ((r8 & 3) * HP + mi * 8) * 2;
        for (int jb = 0; jb < FBLK; jb++) {
            uint32_t a[8];
            ldsm4(h_addr + (jb * 64) * 2, a[0], a[1], a[2], a[3]);
            ldsm4(h_addr + (jb * 64 + 32) * 2, a[4], a[5], a[6], a[7]);
#pragma unroll
            for (int ch = 0; ch < 2; ch++) {
                mbar_wait(bar_full + st * 8, ph);
                const uint32_t wb = sb + OFF_RING + st * STAGE + (warp >> 1) * 8192 + (lane & 15) * 128;
#pragma unroll
                for (int ks = 0; ks < 4; ks++) {
#pragma unroll
                    for (int np = 0; np < 2; np++) {
                        uint32_t b0, b1, b2, b3;
                        const int chunk = (warp & 1) * 4 + np * 2 + (lane >> 4);
                        ldsm4t(wb + ks * 2048 + ((chunk ^ r8) << 4), b0, b1, b2, b3);
                        mma16816(acc[ch][np * 2], a[ks * 2], 0u, a[ks * 2 + 1], 0u, b0, b1);
                        mma16816(acc[ch][np * 2 + 1], a[ks * 2], 0u, a[ks * 2 + 1], 0u, b2, b3);
                    }
                }
                release();
            }
        }
        if (lane < 16) {
            uint32_t* dst = g_pb + ((kHQ + fi) * kB + rr) * kD + (warp >> 1) * 64 + (warp & 1) * 32 + jj * 2;
#pragma unroll
            for (int ch = 0; ch < 2; ch++)
#pragma unroll
                for (int n = 0; n < 4; n++)
                    st_rlx2(dst + ch * 256 + n * 8, tagw(acc[ch][n][0], tag), tagw(acc[ch][n][1], tag));
        }
        TS(15);
        return;
    }

    float* comb = reinterpret_cast<float*>(sp + OFF_COMB);
    float* mx_s = reinterpret_cast<float*>(sp + OFF_MX);
    float* l_s = reinterpret_cast<float*>(sp + OFF_L);
    const int hkv = c >> 4, batch = (c >> 2) & 3;
    {
        const uint32_t nr = tag ^ 1u;
        if (tid < 128) st_rlx(g_q + (tid >> 5) * (kHQ * kDH) + 32 * c + (tid & 31), nr);
        st_rlx2(g_pa + (c * 4 + (rr & 3)) * kDH + (rr >> 2) * 64 + warp * 8 + jj * 2, nr, nr);
        if (tid < 16 && jj == 0) st_rlx2(g_ml + (c * 4 + rr) * 2, nr, nr);
        if (jj < 2) {
            uint32_t* d2 = g_pb + ((c >> 2) * kB + jj * 2) * kD + (c & 3) * 128 + warp * 16 + rr;
            st_rlx(d2, nr);
            st_rlx(d2 + kD, nr);
            st_rlx(d2 + 8, nr);
            st_rlx(d2 + kD + 8, nr);
        }
    }

    {
        float qc[4][4];
#pragma unroll
        for (int n = 0; n < 4; n++)
#pragma unroll
            for (int e = 0; e < 4; e++) qc[n][e] = 0.f;
        uint32_t a[8];
        ldsm4(x_addr + (warp * 64) * 2, a[0], a[1], a[2], a[3]);
        ldsm4(x_addr + (warp * 64 + 32) * 2, a[4], a[5], a[6], a[7]);
        mbar_wait(bar_full + st * 8, ph);
        TS(2);
#pragma unroll
        for (int ks = 0; ks < 4; ks++) {
            const int row = warp * 64 + ks * 16 + (lane & 15);
#pragma unroll
            for (int np = 0; np < 2; np++) {
                uint32_t b0, b1, b2, b3;
                const int chunk = np * 2 + (lane >> 4);
                ldsm4t(sb + OFF_RING + st * STAGE + row * 64 + ((chunk ^ ((row >> 1) & 3)) << 4), b0, b1, b2, b3);
                mma16816(qc[np * 2], a[ks * 2], 0u, a[ks * 2 + 1], 0u, b0, b1);
                mma16816(qc[np * 2 + 1], a[ks * 2], 0u, a[ks * 2 + 1], 0u, b2, b3);
            }
        }
        release();
        if (lane < 16) {
#pragma unroll
            for (int n = 0; n < 4; n++)
                *reinterpret_cast<float2*>(comb + warp * 128 + rr * 32 + n * 8 + jj * 2) = make_float2(qc[n][0], qc[n][1]);
        }
        bar_consumers();
        if (tid < 128) {
            float s = 0.f;
#pragma unroll
            for (int w = 0; w < NCW; w++) s += comb[w * 128 + tid];
            st_rlx(g_q + (tid >> 5) * (kHQ * kDH) + 32 * c + (tid & 31), tagw(s, tag));
            TS(3);
            const uint32_t* qsrc = g_q + batch * (kHQ * kDH) + hkv * 512 + tid * 4;
            uint4 v = ld_rlx4(qsrc);
            int it = 0;
            while (!tag_ok(v, tag)) {
                if (++it > (1 << 21)) __trap();
                __nanosleep(64);
                v = ld_rlx4(qsrc);
            }
            uint2 pk;
            pk.x = pack_bf16(__uint_as_float(v.x), __uint_as_float(v.y));
            pk.y = pack_bf16(__uint_as_float(v.z), __uint_as_float(v.w));
            *reinterpret_cast<uint2*>(sp + OFF_Q + ((tid >> 5) * QP + (tid & 31) * 4) * 2) = pk;
        }
        bar_consumers();
    }
    TS(4);
    uint32_t qa[8];
    {
        const uint32_t qaddr = sb + OFF_Q + ((r8 & 3) * QP + (r8 >> 2) * 64 + mi * 8) * 2;
        ldsm4(qaddr, qa[0], qa[1], qa[2], qa[3]);
        ldsm4(qaddr + 64, qa[4], qa[5], qa[6], qa[7]);
    }

    float o[4][4];
#pragma unroll
    for (int m = 0; m < 4; m++)
#pragma unroll
        for (int e = 0; e < 4; e++) o[m][e] = 0.f;
    float m_run = -INFINITY, l_run = 0.f;
    const uint32_t k_off = (warp * 32 + r8) * 128 + ((mi ^ r8) << 4);
    const uint32_t v_off = (warp * 32 + (mi >> 1) * 8 + r8) * 128 + (((mi & 1) ^ r8) << 4);
    const uint32_t pmask = lane < 16 ? 0x0000ffffu : 0xffff0000u;
    float fsum[4] = {0.f, 0.f, 0.f, 0.f};
    const int bf = c >> 5, col_f = (c & 31) * 16 + (warp & 3) * 4;

    auto scores = [&](float (&sc)[4]) {
        float s[4][4];
        const uint32_t kb = sb + OFF_RING + st * STAGE;
#pragma unroll
        for (int g = 0; g < 4; g++) {
#pragma unroll
            for (int e = 0; e < 4; e++) s[g][e] = 0.f;
            uint32_t b0, b1, b2, b3;
            ldsm4(kb + k_off + g * 1024, b0, b1, b2, b3);
            mma16816(s[g], qa[0], 0u, qa[1], 0u, b0, b1);
            mma16816(s[g], qa[2], 0u, qa[3], 0u, b2, b3);
            ldsm4(kb + (k_off ^ 64u) + g * 1024, b0, b1, b2, b3);
            mma16816(s[g], qa[4], 0u, qa[5], 0u, b0, b1);
            mma16816(s[g], qa[6], 0u, qa[7], 0u, b2, b3);
        }
        release();
#pragma unroll
        for (int g = 0; g < 4; g++) {
            const float v = lane < 16 ? s[g][0] : s[g][1];
            sc[g] = v + __shfl_xor_sync(0xffffffffu, v, 16);
        }
    };
    auto rescale = [&](float m_new) {
        const float alpha = ex2((m_run - m_new) * kScaleLog2);
        l_run *= alpha;
        const float a0 = __shfl_sync(0xffffffffu, alpha, ((2 * jj) & 3) * 4);
        const float a1 = __shfl_sync(0xffffffffu, alpha, ((2 * jj + 1) & 3) * 4);
#pragma unroll
        for (int m = 0; m < 4; m++) {
            o[m][0] *= a0; o[m][1] *= a1; o[m][2] *= a0; o[m][3] *= a1;
        }
        m_run = m_new;
    };
    auto probs = [&](const float (&sc)[4], uint32_t (&pb)[4]) {
        const float mc = m_run * kScaleLog2;
#pragma unroll
        for (int g = 0; g < 4; g++) {
            const float p = ex2(fmaf(sc[g], kScaleLog2, -mc));
            l_run += p;
            pb[g] = pack_bf16(p, p) & pmask;
        }
    };

    for (int t = 0; t < NT - 1; t++) {
        mbar_wait(bar_full + st * 8, ph);
        float sc[4];
        scores(sc);
        float mx = fmaxf(fmaxf(sc[0], sc[1]), fmaxf(sc[2], sc[3]));
        mx = fmaxf(mx, __shfl_xor_sync(0xffffffffu, mx, 1));
        mx = fmaxf(mx, __shfl_xor_sync(0xffffffffu, mx, 2));
        const float m_new = fmaxf(m_run, mx);
        if (__any_sync(0xffffffffu, m_new > m_run)) rescale(m_new);
        uint32_t pb[4];
        probs(sc, pb);
        if (t == NT - 4 && warp < 4) {
            uint4 v = make_uint4(0, 0, 0, 0);
            if (lane < NFFN) v = poll4(g_pb + ((kHQ + lane) * kB + bf) * kD + col_f, tag);
            __syncwarp();
            fsum[0] = __uint_as_float(v.x); fsum[1] = __uint_as_float(v.y);
            fsum[2] = __uint_as_float(v.z); fsum[3] = __uint_as_float(v.w);
#pragma unroll
            for (int e = 0; e < 4; e++) {
                fsum[e] += __shfl_xor_sync(0xffffffffu, fsum[e], 1);
                fsum[e] += __shfl_xor_sync(0xffffffffu, fsum[e], 2);
            }
        }
        mbar_wait(bar_full + st * 8, ph);
        {
            const uint32_t vb = sb + OFF_RING + st * STAGE;
#pragma unroll
            for (int oc = 0; oc < 2; oc++) {
#pragma unroll
                for (int m = 0; m < 4; m++) {
                    uint32_t a0, a1, a2, a3;
                    ldsm4t(vb + ((v_off + oc * 2048) ^ (m * 32)), a0, a1, a2, a3);
                    mma16816(o[m], a0, a1, a2, a3, pb[oc * 2], pb[oc * 2 + 1]);
                }
            }
        }
        release();
    }

    {
        mbar_wait(bar_full + st * 8, ph);
        TS(9);
        float sc[4];
        scores(sc);
        float mx = fmaxf(fmaxf(sc[0], sc[1]), fmaxf(sc[2], sc[3]));
        mx = fmaxf(mx, __shfl_xor_sync(0xffffffffu, mx, 1));
        mx = fmaxf(mx, __shfl_xor_sync(0xffffffffu, mx, 2));
        float m_new = fmaxf(m_run, mx);
        if (lane < 16 && jj == 0) mx_s[warp * 4 + rr] = m_new;
        bar_consumers();
#pragma unroll
        for (int w = 0; w < NCW; w++) m_new = fmaxf(m_new, mx_s[w * 4 + (rr & 3)]);
        if (__any_sync(0xffffffffu, m_new > m_run)) rescale(m_new);
        uint32_t pb[4];
        probs(sc, pb);
        l_run += __shfl_xor_sync(0xffffffffu, l_run, 1);
        l_run += __shfl_xor_sync(0xffffffffu, l_run, 2);
        if (lane < 16 && jj == 0) l_s[warp * 4 + rr] = l_run;
        uint4* pbuf = reinterpret_cast<uint4*>(sp + OFF_X);
        pbuf[tid] = make_uint4(pb[0], pb[1], pb[2], pb[3]);
        {
            float* dst = comb + warp * COMB_W + jj * 8 + rr;
#pragma unroll
            for (int m = 0; m < 4; m++)
#pragma unroll
                for (int e = 0; e < 4; e++) dst[(2 * m + (e >> 1)) * 80 + (e & 1) * 48] = o[m][e];
        }
        bar_consumers();
        if (tid < 16 && jj == 0) {
            float l = 0.f;
#pragma unroll
            for (int w = 0; w < NCW; w++) l += l_s[w * 4 + rr];
            st_rlx2(g_ml + (c * 4 + rr) * 2, tagw(m_run, tag), tagw(l, tag));
        }
        float2 prev;
        {
            const float* src = comb + warp * 80 + (rr & 1) * 48 + (rr >> 1) * 8 + jj * 2;
            prev = *reinterpret_cast<const float2*>(src);
#pragma unroll
            for (int w = 1; w < NCW; w++) {
                const float2 v = *reinterpret_cast<const float2*>(src + w * COMB_W);
                prev.x += v.x; prev.y += v.y;
            }
        }
        uint4 pf[NVP];
#pragma unroll
        for (int j = 0; j < NVP; j++) pf[j] = pbuf[j * 32 + lane];
        float acc[4][4];
#pragma unroll
        for (int u = 0; u < 4; u++)
#pragma unroll
            for (int e = 0; e < 4; e++) acc[u][e] = 0.f;
        acc[0][0] = prev.x; acc[0][1] = prev.y;
        const uint32_t vb = sb + OFF_RING + st * STAGE + lane * 128 + ((warp ^ r8) << 4);
#pragma unroll
        for (int j = 0; j < NVP; j++) {
            mbar_wait(bar_vp + j * 8, 0);
            uint32_t b0, b1, b2, b3;
            ldsm4t(vb + j * (STAGE / NVP), b0, b1, b2, b3);
            mma16816(acc[(j & 1) * 2], pf[j].x, 0u, pf[j].y, 0u, b0, b1);
            mma16816(acc[(j & 1) * 2 + 1], pf[j].z, 0u, pf[j].w, 0u, b2, b3);
        }
        TS(10);
        advance();
        st_rlx2(g_pa + (c * 4 + (rr & 3)) * kDH + (rr >> 2) * 64 + warp * 8 + jj * 2,
                tagw((acc[0][0] + acc[1][0]) + (acc[2][0] + acc[3][0]), tag),
                tagw((acc[0][1] + acc[1][1]) + (acc[2][1] + acc[3][1]), tag));
    }
    TS(11);

    uint32_t wf[8][4];
    auto load_wo = [&]() {
        const uint32_t wb = sb + OFF_RING + st * STAGE + (warp >> 2) * 16384 + ((mi >> 1) * 8 + r8) * 128 +
                            ((((warp & 3) * 2 + (mi & 1)) ^ r8) << 4);
#pragma unroll
        for (int ks = 0; ks < 8; ks++) ldsm4t(wb + ks * 2048, wf[ks][0], wf[ks][1], wf[ks][2], wf[ks][3]);
    };
    {
        const int hh = (c >> 2) & 3;
        const uint32_t* pm = g_ml + (((c & ~15) | ((warp >> 1) << 2)) * 4 + hh) * 2;
        const uint32_t* po = g_pa + (((c & ~15) | ((warp >> 1) << 2)) * 4 + hh) * kDH + (warp & 1) * 64 + lane * 2;
        uint2 v[4];
        auto load_pa = [&](uint2 (&d)[4]) {
#pragma unroll
            for (int s = 0; s < 4; s++) d[s] = ld_rlx2(po + s * (4 * kDH));
        };
        auto pa_ok = [&](const uint2 (&d)[4]) {
            return ((((d[0].x ^ tag) | (d[0].y ^ tag) | (d[1].x ^ tag) | (d[1].y ^ tag) | (d[2].x ^ tag) | (d[2].y ^ tag) |
                      (d[3].x ^ tag) | (d[3].y ^ tag)) & 1u) == 0);
        };
        spin(DLY_M);
        uint2 mlv[4];
#pragma unroll
        for (int s = 0; s < 4; s++) mlv[s] = ld_rlx2(pm + s * 8);
        int it = 0;
        while (!pa_ok(mlv)) {
            if (++it > (1 << 21)) __trap();
#pragma unroll
            for (int s = 0; s < 4; s++) mlv[s] = ld_rlx2(pm + s * 8);
        }
        TS(19);
        float w4[4];
        {
            const float ms[4] = {__uint_as_float(mlv[0].x), __uint_as_float(mlv[1].x), __uint_as_float(mlv[2].x), __uint_as_float(mlv[3].x)};
            const float ls[4] = {__uint_as_float(mlv[0].y), __uint_as_float(mlv[1].y), __uint_as_float(mlv[2].y), __uint_as_float(mlv[3].y)};
            const float M = fmaxf(fmaxf(ms[0], ms[1]), fmaxf(ms[2], ms[3]));
            float L = 0.f;
#pragma unroll
            for (int s = 0; s < 4; s++) {
                w4[s] = ex2((ms[s] - M) * kScaleLog2);
                L = fmaf(w4[s], ls[s], L);
            }
            const float inv = 1.f / L;
#pragma unroll
            for (int s = 0; s < 4; s++) w4[s] *= inv;
        }
        mbar_wait(bar_full + st * 8, ph);
        TS(20);
        load_pa(v);
        load_wo();
        while (!__all_sync(0xffffffffu, pa_ok(v))) {
            if (++it > (1 << 21)) __trap();
            load_pa(v);
        }
        TS(12);
        float z0 = 0.f, z1 = 0.f;
#pragma unroll
        for (int s = 0; s < 4; s++) {
            z0 = fmaf(w4[s], __uint_as_float(v[s].x), z0);
            z1 = fmaf(w4[s], __uint_as_float(v[s].y), z1);
        }
        *reinterpret_cast<uint32_t*>(sp + OFF_Q + ((warp >> 1) * QP + (warp & 1) * 64 + lane * 2) * 2) = pack_bf16(z0, z1);
    }
    bar_consumers();
    {
        const uint32_t oaddr = sb + OFF_Q + ((r8 & 3) * QP + mi * 8) * 2;
        float acc[4][4];
#pragma unroll
        for (int u = 0; u < 4; u++)
#pragma unroll
            for (int e = 0; e < 4; e++) acc[u][e] = 0.f;
#pragma unroll
        for (int kp = 0; kp < 4; kp++) {
            uint32_t b0, b1, b2, b3;
            ldsm4(oaddr + kp * 64, b0, b1, b2, b3);
            mma16816(acc[(kp & 1) * 2], wf[kp * 2][0], wf[kp * 2][1], wf[kp * 2][2], wf[kp * 2][3], b0, b1);
            mma16816(acc[(kp & 1) * 2 + 1], wf[kp * 2 + 1][0], wf[kp * 2 + 1][1], wf[kp * 2 + 1][2], wf[kp * 2 + 1][3], b2, b3);
        }
        if (jj < 2) {
            uint32_t* dst = g_pb + ((c >> 2) * kB + jj * 2) * kD + (c & 3) * 128 + warp * 16 + rr;
            st_rlx(dst, tagw((acc[0][0] + acc[1][0]) + (acc[2][0] + acc[3][0]), tag));
            st_rlx(dst + kD, tagw((acc[0][1] + acc[1][1]) + (acc[2][1] + acc[3][1]), tag));
            st_rlx(dst + 8, tagw((acc[0][2] + acc[1][2]) + (acc[2][2] + acc[3][2]), tag));
            st_rlx(dst + kD + 8, tagw((acc[0][3] + acc[1][3]) + (acc[2][3] + acc[3][3]), tag));
        }
    }
    TS(13);
    if (warp < 4) {
        const uint32_t* pbp = g_pb + (lane * kB + bf) * kD + col_f;
        spin(DLY_B);
        const uint4 v = poll4(pbp, tag);
        __syncwarp();
        TS(14);
        const float a[4] = {__uint_as_float(v.x), __uint_as_float(v.y), __uint_as_float(v.z), __uint_as_float(v.w)};
        const bool b0 = lane & 1, b1 = lane & 2;
        const float s0 = b0 ? a[0] : a[1], k0 = b0 ? a[1] : a[0];
        const float s1 = b0 ? a[2] : a[3], k1 = b0 ? a[3] : a[2];
        const float r0 = k0 + __shfl_xor_sync(0xffffffffu, s0, 1);
        const float r1 = k1 + __shfl_xor_sync(0xffffffffu, s1, 1);
        float r = (b1 ? r1 : r0) + __shfl_xor_sync(0xffffffffu, b1 ? r0 : r1, 2);
        r += __shfl_xor_sync(0xffffffffu, r, 4);
        r += __shfl_xor_sync(0xffffffffu, r, 8);
        r += __shfl_xor_sync(0xffffffffu, r, 16);
        if (lane < 4) {
            const float g = misc_f[0];
            const float f = b1 ? (b0 ? fsum[3] : fsum[2]) : (b0 ? fsum[1] : fsum[0]);
            prm.out[bf * kD + col_f + lane] = __float2bfloat16_rn(g * r + (1.f - g) * f);
            if (c == 0 && warp == 0 && lane == 0) {
                asm volatile("st.relaxed.gpu.global.u32 [%0], %1;" ::"l"(&g_epoch), "r"(epoch + 1u) : "memory");
            }
        }
        TS(15);
    }
}

typedef CUresult (*EncodeFn)(CUtensorMap*, CUtensorMapDataType, cuuint32_t, void*, const cuuint64_t*, const cuuint64_t*,
                             const cuuint32_t*, const cuuint32_t*, CUtensorMapInterleave, CUtensorMapSwizzle,
                             CUtensorMapL2promotion, CUtensorMapFloatOOBfill);

void encode2d(EncodeFn enc, CUtensorMap* m, const void* base, uint64_t cols, uint64_t rows, uint64_t pitch_bytes,
              uint32_t box_cols, uint32_t box_rows, CUtensorMapSwizzle swz) {
    cuuint64_t gd[2] = {cols, rows};
    cuuint64_t gs[1] = {pitch_bytes};
    cuuint32_t bd[2] = {box_cols, box_rows};
    cuuint32_t es[2] = {1, 1};
    enc(m, CU_TENSOR_MAP_DATA_TYPE_BFLOAT16, 2, const_cast<void*>(base), gd, gs, bd, es, CU_TENSOR_MAP_INTERLEAVE_NONE,
        swz, CU_TENSOR_MAP_L2_PROMOTION_L2_128B, CU_TENSOR_MAP_FLOAT_OOB_FILL_NONE);
}

}

extern "C" void kernel_launch(void* const* d_in, const int* in_sizes, int n_in, void* d_out, int out_size) {
    (void)in_sizes; (void)n_in; (void)out_size;
    static EncodeFn enc = nullptr;
    if (!enc) {
        void* fn = nullptr;
        cudaDriverEntryPointQueryResult qr;
        cudaGetDriverEntryPoint("cuTensorMapEncodeTiled", &fn, cudaEnableDefault, &qr);
        enc = reinterpret_cast<EncodeFn>(fn);
        cudaFuncSetAttribute(fused_decode_kernel, cudaFuncAttributeMaxDynamicSharedMemorySize, SMEM_BYTES);
    }
    CUtensorMap tk, tv, tvp, twq, two, twg, twu, twd;
    encode2d(enc, &tk, d_in[1], 64, (uint64_t)kB * kHKV * kSK * 2, 128, 64, 256, CU_TENSOR_MAP_SWIZZLE_128B);
    encode2d(enc, &tv, d_in[2], 64, (uint64_t)kB * kHKV * kSK * 2, 128, 64, 256, CU_TENSOR_MAP_SWIZZLE_128B);
    encode2d(enc, &tvp, d_in[2], 64, (uint64_t)kB * kHKV * kSK * 2, 128, 64, 256 / NVP, CU_TENSOR_MAP_SWIZZLE_128B);
    encode2d(enc, &twq, d_in[3], kHQ * kDH, kD, kHQ * kDH * 2, 32, 256, CU_TENSOR_MAP_SWIZZLE_64B);
    encode2d(enc, &two, d_in[4], kD, kHQ * kDH, kD * 2, 64, 128, CU_TENSOR_MAP_SWIZZLE_128B);
    encode2d(enc, &twg, d_in[6], kF, kD, kF * 2, 64, 256, CU_TENSOR_MAP_SWIZZLE_128B);
    encode2d(enc, &twu, d_in[7], kF, kD, kF * 2, 64, 256, CU_TENSOR_MAP_SWIZZLE_128B);
    encode2d(enc, &twd, d_in[8], kD, kF, kD * 2, 64, 64, CU_TENSOR_MAP_SWIZZLE_128B);
    Params prm;
    prm.x = reinterpret_cast<const __nv_bfloat16*>(d_in[0]);
    prm.gate_w = reinterpret_cast<const __nv_bfloat16*>(d_in[9]);
    prm.out = reinterpret_cast<__nv_bfloat16*>(d_out);
    fused_decode_kernel<<<NCTA, NTHREADS, SMEM_BYTES>>>(tk, tv, tvp, twq, two, twg, twu, twd, prm);
}
```

```cpp
#include <cuda_runtime.h>
#include <cuda_bf16.h>
#include <cuda.h>
#include <stdint.h>

#define EVICT_FIRST 1
#define WIN 2
#define INIT_WRITES 1
#define PACE 1
#define PACE_K 16
#define PACE_L0 (-32)
#define PACE_MAX 2000
#define WO_AT 7
#define DLY_M 650
#define DLY_B 250

namespace {

constexpr int kB = 4, kD = 512, kHQ = 32, kHKV = 8, kDH = 128, kSK = 16384, kF = 1792;
constexpr int NATT = 128;
constexpr int NFFN = 4;
constexpr int NCTA = NATT + NFFN;
constexpr int NSTAGE = 6;
constexpr int STAGE = 32768;
constexpr int NCW = 8;
constexpr int NTHREADS = (NCW + 1) * 32;
constexpr int KEYS_PER_CTA = kSK / 4;
constexpr int NT = KEYS_PER_CTA / 128;
constexpr int ATT_STAGES = 2 + 2 * NT;
constexpr int FCOLS = kF / NFFN;
constexpr int FBLK = FCOLS / 64;
constexpr int FFN_STAGES = 4 * FBLK + 2 * FBLK;

constexpr int XP = 520;
constexpr int QP = 136;
constexpr int HP = FCOLS + 8;
constexpr int COMB_W = 640;
constexpr int OFF_RING = 0;
constexpr int OFF_COMB = NSTAGE * STAGE;
constexpr int OFF_X = OFF_COMB + NCW * COMB_W * 4;
constexpr int OFF_Q = OFF_X + kB * XP * 2;
constexpr int OFF_H = OFF_Q + kB * QP * 2;
constexpr int OFF_MX = OFF_H + kB * HP * 2;
constexpr int OFF_L = OFF_MX + NCW * 4 * 4;
constexpr int OFF_MISC = OFF_L + NCW * 4 * 4;
constexpr int OFF_BAR = OFF_MISC + 16;
constexpr int NVP = 8;
constexpr int SMEM_USED = OFF_BAR + (2 * NSTAGE + NVP) * 8;
constexpr int SMEM_BYTES = SMEM_USED + 1024;
static_assert(SMEM_BYTES <= 232448, "smem");
static_assert(OFF_X % 16 == 0 && OFF_Q % 16 == 0 && OFF_H % 16 == 0 && OFF_BAR % 8 == 0, "align");

constexpr float kScaleLog2 = 0.08838834764831845f * 1.4426950408889634f;

__device__ uint32_t g_epoch;
__device__ __align__(128) uint32_t g_prog[2 * 32];
__device__ __align__(128) uint32_t g_q[kB * kHQ * kDH];
__device__ __align__(128) uint32_t g_pa[NATT * 4 * kDH];
__device__ __align__(128) uint32_t g_ml[NATT * 4 * 2];
__device__ __align__(128) uint32_t g_pb[(kHQ + NFFN) * kB * kD];

#define TS(i)
#define TSP(i)

__device__ __forceinline__ uint32_t smem_u32(const void* p) { return (uint32_t)__cvta_generic_to_shared(p); }
__device__ __forceinline__ void mbar_init(uint32_t bar, uint32_t cnt) {
    asm volatile("mbarrier.init.shared::cta.b64 [%0], %1;" ::"r"(bar), "r"(cnt));
}
__device__ __forceinline__ void mbar_expect_tx(uint32_t bar, uint32_t bytes) {
    asm volatile("mbarrier.arrive.expect_tx.shared::cta.b64 _, [%0], %1;" ::"r"(bar), "r"(bytes) : "memory");
}
__device__ __forceinline__ void mbar_arrive(uint32_t bar) {
    asm volatile("mbarrier.arrive.shared::cta.b64 _, [%0];" ::"r"(bar) : "memory");
}
__device__ __forceinline__ bool mbar_try_wait(uint32_t bar, uint32_t parity) {
    uint32_t ok;
    asm volatile("{\n.reg .pred p;\nmbarrier.try_wait.parity.shared::cta.b64 p, [%1], %2;\nselp.u32 %0, 1, 0, p;\n}"
                 : "=r"(ok) : "r"(bar), "r"(parity) : "memory");
    return ok;
}
__device__ __forceinline__ void mbar_wait(uint32_t bar, uint32_t parity) {
    if (mbar_try_wait(bar, parity)) return;
    const long long t0 = clock64();
    while (!mbar_try_wait(bar, parity)) {
        if (clock64() - t0 > 4000000000LL) __trap();
    }
}
__device__ __forceinline__ void tma2d(uint32_t dst, const CUtensorMap* m, int c0, int c1, uint32_t bar) {
    asm volatile("cp.async.bulk.tensor.2d.shared::cluster.global.mbarrier::complete_tx::bytes [%0], [%1, {%3, %4}], [%2];"
                 ::"r"(dst), "l"(m), "r"(bar), "r"(c0), "r"(c1) : "memory");
}
__device__ __forceinline__ void tma2d_hint(uint32_t dst, const CUtensorMap* m, int c0, int c1, uint32_t bar, uint64_t pol) {
    asm volatile("cp.async.bulk.tensor.2d.shared::cluster.global.mbarrier::complete_tx::bytes.L2::cache_hint"
                 " [%0], [%1, {%3, %4}], [%2], %5;"
                 ::"r"(dst), "l"(m), "r"(bar), "r"(c0), "r"(c1), "l"(pol) : "memory");
}
__device__ __forceinline__ void prefetch_tmap(const CUtensorMap* m) {
    asm volatile("prefetch.tensormap [%0];" ::"l"(m) : "memory");
}
__device__ __forceinline__ void ldsm4(uint32_t addr, uint32_t& r0, uint32_t& r1, uint32_t& r2, uint32_t& r3) {
    asm volatile("ldmatrix.sync.aligned.m8n8.x4.shared.b16 {%0,%1,%2,%3}, [%4];"
                 : "=r"(r0), "=r"(r1), "=r"(r2), "=r"(r3) : "r"(addr) : "memory");
}
__device__ __forceinline__ void ldsm4t(uint32_t addr, uint32_t& r0, uint32_t& r1, uint32_t& r2, uint32_t& r3) {
    asm volatile("ldmatrix.sync.aligned.m8n8.x4.trans.shared.b16 {%0,%1,%2,%3}, [%4];"
                 : "=r"(r0), "=r"(r1), "=r"(r2), "=r"(r3) : "r"(addr) : "memory");
}
__device__ __forceinline__ void mma16816(float (&c)[4], uint32_t a0, uint32_t a1, uint32_t a2, uint32_t a3,
                                         uint32_t b0, uint32_t b1) {
    asm volatile("mma.sync.aligned.m16n8k16.row.col.f32.bf16.bf16.f32 {%0,%1,%2,%3}, {%4,%5,%6,%7}, {%8,%9}, {%0,%1,%2,%3};"
                 : "+f"(c[0]), "+f"(c[1]), "+f"(c[2]), "+f"(c[3])
                 : "r"(a0), "r"(a1), "r"(a2), "r"(a3), "r"(b0), "r"(b1));
}
__device__ __forceinline__ float ex2(float x) {
    float y;
    asm("ex2.approx.ftz.f32 %0, %1;" : "=f"(y) : "f"(x));
    return y;
}
__device__ __forceinline__ uint32_t pack_bf16(float lo, float hi) {
    uint32_t r;
    asm("cvt.rn.bf16x2.f32 %0, %1, %2;" : "=r"(r) : "f"(hi), "f"(lo));
    return r;
}
__device__ __forceinline__ float bf16_round(float v) { return __bfloat162float(__float2bfloat16_rn(v)); }
__device__ __forceinline__ void spin(int cycles) {
    const uint32_t t0 = clock();
    while ((int)(clock() - t0) < cycles) {}
}
__device__ __forceinline__ void bar_consumers() { asm volatile("bar.sync 1, 256;" ::: "memory"); }

__device__ __forceinline__ uint32_t tagw(float v, uint32_t tag) { return (__float_as_uint(v) & ~1u) | tag; }
__device__ __forceinline__ void st_rlx(uint32_t* p, uint32_t v) {
    asm volatile("st.relaxed.gpu.global.u32 [%0], %1;" ::"l"(p), "r"(v) : "memory");
}
__device__ __forceinline__ void st_rlx2(uint32_t* p, uint32_t a, uint32_t b) {
    asm volatile("st.relaxed.gpu.global.v2.u32 [%0], {%1,%2};" ::"l"(p), "r"(a), "r"(b) : "memory");
}
__device__ __forceinline__ uint4 ld_rlx4(const uint32_t* p) {
    uint4 v;
    asm volatile("ld.relaxed.gpu.global.v4.u32 {%0,%1,%2,%3}, [%4];"
                 : "=r"(v.x), "=r"(v.y), "=r"(v.z), "=r"(v.w) : "l"(p) : "memory");
    return v;
}
__device__ __forceinline__ uint2 ld_rlx2(const uint32_t* p) {
    uint2 v;
    asm volatile("ld.relaxed.gpu.global.v2.u32 {%0,%1}, [%2];" : "=r"(v.x), "=r"(v.y) : "l"(p) : "memory");
    return v;
}
__device__ __forceinline__ bool tag_ok(uint4 v, uint32_t tag) {
    return (((v.x ^ tag) | (v.y ^ tag) | (v.z ^ tag) | (v.w ^ tag)) & 1u) == 0;
}
__device__ __forceinline__ uint4 poll4(const uint32_t* p, uint32_t tag) {
    uint4 v = ld_rlx4(p);
    int it = 0;
    while (!tag_ok(v, tag)) {
        if (++it > (1 << 21)) __trap();
        v = ld_rlx4(p);
    }
    return v;
}

struct Params {
    const __nv_bfloat16* x;
    const __nv_bfloat16* gate_w;
    __nv_bfloat16* out;
};

__global__ void __launch_bounds__(NTHREADS, 1)
fused_decode_kernel(const __grid_constant__ CUtensorMap tm_k, const __grid_constant__ CUtensorMap tm_v,
                    const __grid_constant__ CUtensorMap tm_vp,
                    const __grid_constant__ CUtensorMap tm_wq, const __grid_constant__ CUtensorMap tm_wo,
                    const __grid_constant__ CUtensorMap tm_wg, const __grid_constant__ CUtensorMap tm_wu,
                    const __grid_constant__ CUtensorMap tm_wd, const Params prm) {
    extern __shared__ uint8_t smem_raw[];
    const uint32_t sraw = smem_u32(smem_raw);
    uint32_t sb = (sraw + 1023u) & ~1023u;
    uint64_t p_wq = reinterpret_cast<uint64_t>(&tm_wq), p_k = reinterpret_cast<uint64_t>(&tm_k);
    asm volatile("" : "+r"(sb), "+l"(p_wq), "+l"(p_k));
    uint8_t* sp = smem_raw + (((sraw + 1023u) & ~1023u) - sraw);
    const int tid = threadIdx.x, warp = tid >> 5, lane = tid & 31;
    const int c = blockIdx.x;
    const bool is_ffn = c >= NATT;
    const uint32_t bar_full = sb + OFF_BAR, bar_empty = bar_full + NSTAGE * 8, bar_vp = bar_empty + NSTAGE * 8;

    TS(0);
    if (warp == NCW) {
        uint64_t pol0;
        asm volatile("createpolicy.fractional.L2::evict_first.b64 %0, 1.0;" : "=l"(pol0));
        if (lane == 0) {
            for (int s = 0; s < WIN; s++) mbar_init(bar_full + s * 8, 1);
            asm volatile("fence.proxy.async.shared::cta;" ::: "memory");
            if (!is_ffn) {
                static_assert(WIN == 2, "the prologue issues stage 0 (wq) and stage 1 (first K tile)");
                const int l0 = (((c >> 2) & 3) * kHKV + (c >> 4)) * (kSK * 2) + (c & 3) * (KEYS_PER_CTA * 2);
                mbar_expect_tx(bar_full, STAGE);
                tma2d(sb + OFF_RING, reinterpret_cast<const CUtensorMap*>(p_wq), 32 * c, 0, bar_full);
                tma2d(sb + OFF_RING + STAGE / 2, reinterpret_cast<const CUtensorMap*>(p_wq), 32 * c, 256, bar_full);
                mbar_expect_tx(bar_full + 8, STAGE);
                tma2d_hint(sb + OFF_RING + STAGE, reinterpret_cast<const CUtensorMap*>(p_k), 0, l0, bar_full + 8, pol0);
            }
        }
        const int nst = is_ffn ? FFN_STAGES : ATT_STAGES;
        const int kv_line0 = (((c >> 2) & 3) * kHKV + (c >> 4)) * (kSK * 2) + (c & 3) * (KEYS_PER_CTA * 2);
        const int f0 = (c - NATT) * FCOLS;
        uint64_t pol;
        asm volatile("createpolicy.fractional.L2::evict_first.b64 %0, 1.0;" : "=l"(pol));
        auto issue = [&](int i, int s) {
            const uint32_t bar = bar_full + s * 8, dst = sb + OFF_RING + s * STAGE;
            if (!is_ffn && i == 2 * NT) {
#pragma unroll 1
                for (int j = 0; j < NVP; j++) {
                    mbar_expect_tx(bar_vp + j * 8, STAGE / NVP);
                    tma2d_hint(dst + j * (STAGE / NVP), &tm_vp, 0, kv_line0 + (NT - 1) * 256 + j * (256 / NVP), bar_vp + j * 8, pol);
                }
                return;
            }
            mbar_expect_tx(bar, STAGE);
            if (!is_ffn) {
                if (i == 0) {
                    tma2d(dst, &tm_wq, 32 * c, 0, bar);
                    tma2d(dst + STAGE / 2, &tm_wq, 32 * c, 256, bar);
                } else if (i <= 2 * NT) {
                    const int t = (i - 1) >> 1;
                    tma2d_hint(dst, ((i - 1) & 1) ? &tm_v : &tm_k, 0, kv_line0 + t * 256, bar, pol);
                } else {
                    tma2d(dst, &tm_wo, 128 * (c & 3), 128 * (c >> 2), bar);
                    tma2d(dst + STAGE / 2, &tm_wo, 128 * (c & 3) + 64, 128 * (c >> 2), bar);
                }
            } else {
                if (i < 4 * FBLK) {
                    tma2d(dst, (i & 2) ? &tm_wu : &tm_wg, f0 + 64 * (i >> 2), 256 * (i & 1), bar);
                } else {
                    const int ii = i - 4 * FBLK;
#pragma unroll
                    for (int blk = 0; blk < 4; blk++)
                        tma2d(dst + blk * 8192, &tm_wd, 256 * (ii & 1) + 64 * blk, f0 + 64 * (ii >> 1), bar);
                }
            }
        };
        if (lane == 0) {
            TSP(16);
            if (is_ffn) for (int s = 0; s < WIN; s++) issue(s, s);
            TSP(17);
            for (int s = 0; s < NSTAGE; s++) {
                if (s >= WIN) mbar_init(bar_full + s * 8, 1);
                mbar_init(bar_empty + s * 8, NCW);
            }
            for (int s = 0; s < NVP; s++) mbar_init(bar_vp + s * 8, 1);
            asm volatile("fence.mbarrier_init.release.cluster;" ::: "memory");
            asm volatile("fence.proxy.async.shared::cta;" ::: "memory");
        }
        __syncthreads();
        if (lane == 0) {
            int s = WIN % NSTAGE, sw = 0;
            uint32_t ph = WIN == NSTAGE ? 0 : 1, phw = 0;
            const uint32_t ep = *reinterpret_cast<volatile uint32_t*>(sp + OFF_MISC + 4);
            uint32_t* prog = g_prog + (ep & 1u) * 32;
            if (c == 0) st_rlx(g_prog + ((ep + 1u) & 1u) * 32, 0u);
            uint32_t r_old = 0;
            int dly = 0;
            for (int i = WIN; i < nst; i++) {
                mbar_wait(bar_full + sw * 8, phw);
                const uint32_t t0 = clock();
                if (!is_ffn && (i & 1)) {
                    if (i >= 5) dly = min(max((64 * (i - 3) - (int)r_old - 1 - (PACE_L0)) * PACE_K, 0), PACE_MAX);
                    asm volatile("atom.relaxed.gpu.global.add.u32 %0, [%1], 1;" : "=r"(r_old) : "l"(prog) : "memory");
                }
                if (i >= NSTAGE) mbar_wait(bar_empty + s * 8, ph);
                if (WO_AT >= 0 && !is_ffn && i == ATT_STAGES - 1) {
                    mbar_wait(bar_vp + (WO_AT < 0 ? 0 : WO_AT) * 8, 0);
                }
                while ((int)(clock() - t0) < dly) {}
                issue(i, s);
                if (++s == NSTAGE) { s = 0; ph ^= 1; }
                if (++sw == NSTAGE) { sw = 0; phw ^= 1; }
            }
            TSP(18);
        }
        return;
    }

    {
        const uint4 xv = __ldg(reinterpret_cast<const uint4*>(prm.x) + tid);
        *reinterpret_cast<uint4*>(sp + OFF_X + ((tid >> 6) * XP + (tid & 63) * 8) * 2) = xv;
    }
    float* misc_f = reinterpret_cast<float*>(sp + OFF_MISC);
    uint32_t* misc_u = reinterpret_cast<uint32_t*>(sp + OFF_MISC);
    if (tid == 0) {
        uint32_t e;
        asm volatile("ld.relaxed.gpu.global.u32 %0, [%1];" : "=r"(e) : "l"(&g_epoch) : "memory");
        misc_u[1] = e;
    }
    if (warp == NCW - 1 && !is_ffn) {
        const int bf = c >> 5;
        const uint4* xp = reinterpret_cast<const uint4*>(prm.x + bf * kD) + lane * 2;
        const uint4* gp = reinterpret_cast<const uint4*>(prm.gate_w) + lane * 2;
        float acc = 0.f;
#pragma unroll
        for (int u = 0; u < 2; u++) {
            const uint4 a = __ldg(xp + u), g = __ldg(gp + u);
            const uint32_t aw[4] = {a.x, a.y, a.z, a.w}, gw[4] = {g.x, g.y, g.z, g.w};
#pragma unroll
            for (int e = 0; e < 4; e++) {
                acc = fmaf(__uint_as_float(aw[e] << 16), __uint_as_float(gw[e] << 16), acc);
                acc = fmaf(__uint_as_float(aw[e] & 0xffff0000u), __uint_as_float(gw[e] & 0xffff0000u), acc);
            }
        }
#pragma unroll
        for (int o = 16; o > 0; o >>= 1) acc += __shfl_xor_sync(0xffffffffu, acc, o);
        if (lane == 0) misc_f[0] = 1.f / (1.f + __expf(-acc));
    }
    __syncthreads();
    TS(1);
    const uint32_t epoch = misc_u[1];
    const uint32_t tag = (epoch + 1u) & 1u;

    const int r8 = lane & 7, mi = lane >> 3;
    const int rr = lane >> 2, jj = lane & 3;
    int st = 0;
    uint32_t ph = 0;
    auto advance = [&]() { if (++st == NSTAGE) { st = 0; ph ^= 1; } };
    auto release = [&]() {
        __syncwarp();
        if (lane == 0) mbar_arrive(bar_empty + st * 8);
        advance();
    };
    const uint32_t x_addr = sb + OFF_X + ((r8 & 3) * XP + mi * 8) * 2;

    if (is_ffn) {
        const int fi = c - NATT;
        if (lane < 16) {
            uint32_t* dst = g_pb + ((kHQ + fi) * kB + rr) * kD + (warp >> 1) * 64 + (warp & 1) * 32 + jj * 2;
#pragma unroll
            for (int ch = 0; ch < 2; ch++)
#pragma unroll
                for (int n = 0; n < 4; n++) st_rlx2(dst + ch * 256 + n * 8, tag ^ 1u, tag ^ 1u);
        }
        for (int jb = 0; jb < FBLK; jb++) {
            float gu[2][2][4];
#pragma unroll
            for (int m = 0; m < 2; m++) {
#pragma unroll
                for (int e = 0; e < 4; e++) gu[m][0][e] = gu[m][1][e] = 0.f;
#pragma unroll
                for (int kh = 0; kh < 2; kh++) {
                    mbar_wait(bar_full + st * 8, ph);
                    const uint32_t wb = sb + OFF_RING + st * STAGE + lane * 128 + ((warp ^ r8) << 4);
#pragma unroll
                    for (int kk = 0; kk < 8; kk++) {
                        uint32_t b0, b1, b2, b3, a0, a1, a2, a3;
                        ldsm4t(wb + kk * 4096, b0, b1, b2, b3);
                        ldsm4(x_addr + (kh * 256 + kk * 32) * 2, a0, a1, a2, a3);
                        mma16816(gu[m][0], a0, 0u, a1, 0u, b0, b1);
                        mma16816(gu[m][1], a2, 0u, a3, 0u, b2, b3);
                    }
                    release();
                }
            }
            const float g0 = bf16_round(gu[0][0][0] + gu[0][1][0]), g1 = bf16_round(gu[0][0][1] + gu[0][1][1]);
            const float u0 = bf16_round(gu[1][0][0] + gu[1][1][0]), u1 = bf16_round(gu[1][0][1] + gu[1][1][1]);
            const float h0 = (g0 > 0.f ? g0 : 0.f) * u0, h1 = (g1 > 0.f ? g1 : 0.f) * u1;
            if (lane < 16)
                *reinterpret_cast<uint32_t*>(sp + OFF_H + (rr * HP + jb * 64 + warp * 8 + jj * 2) * 2) = pack_bf16(h0, h1);
        }
        bar_consumers();
        TS(10);
        float acc[2][4][4];
#pragma unroll
        for (int ch = 0; ch < 2; ch++)
#pragma unroll
            for (int n = 0; n < 4; n++)
#pragma unroll
                for (int e = 0; e < 4; e++) acc[ch][n][e] = 0.f;
        const uint32_t h_addr = sb + OFF_H + ((r8 & 3) * HP + mi * 8) * 2;
        for (int jb = 0; jb < FBLK; jb++) {
            uint32_t a[8];
            ldsm4(h_addr + (jb * 64) * 2, a[0], a[1], a[2], a[3]);
            ldsm4(h_addr + (jb * 64 + 32) * 2, a[4], a[5], a[6], a[7]);
#pragma unroll
            for (int ch = 0; ch < 2; ch++) {
                mbar_wait(bar_full + st * 8, ph);
                const uint32_t wb = sb + OFF_RING + st * STAGE + (warp >> 1) * 8192 + (lane & 15) * 128;
#pragma unroll
                for (int ks = 0; ks < 4; ks++) {
#pragma unroll
                    for (int np = 0; np < 2; np++) {
                        uint32_t b0, b1, b2, b3;
                        const int chunk = (warp & 1) * 4 + np * 2 + (lane >> 4);
                        ldsm4t(wb + ks * 2048 + ((chunk ^ r8) << 4), b0, b1, b2, b3);
                        mma16816(acc[ch][np * 2], a[ks * 2], 0u, a[ks * 2 + 1], 0u, b0, b1);
                        mma16816(acc[ch][np * 2 + 1], a[ks * 2], 0u, a[ks * 2 + 1], 0u, b2, b3);
                    }
                }
                release();
            }
        }
        if (lane < 16) {
            uint32_t* dst = g_pb + ((kHQ + fi) * kB + rr) * kD + (warp >> 1) * 64 + (warp & 1) * 32 + jj * 2;
#pragma unroll
            for (int ch = 0; ch < 2; ch++)
#pragma unroll
                for (int n = 0; n < 4; n++)
                    st_rlx2(dst + ch * 256 + n * 8, tagw(acc[ch][n][0], tag), tagw(acc[ch][n][1], tag));
        }
        TS(15);
        return;
    }

    float* comb = reinterpret_cast<float*>(sp + OFF_COMB);
    float* mx_s = reinterpret_cast<float*>(sp + OFF_MX);
    float* l_s = reinterpret_cast<float*>(sp + OFF_L);
    const int hkv = c >> 4, batch = (c >> 2) & 3;
    {
        const uint32_t nr = tag ^ 1u;
        if (tid < 128) st_rlx(g_q + (tid >> 5) * (kHQ * kDH) + 32 * c + (tid & 31), nr);
        st_rlx2(g_pa + (c * 4 + (rr & 3)) * kDH + (rr >> 2) * 64 + warp * 8 + jj * 2, nr, nr);
        if (tid < 16 && jj == 0) st_rlx2(g_ml + (c * 4 + rr) * 2, nr, nr);
        if (jj < 2) {
            uint32_t* d2 = g_pb + ((c >> 2) * kB + jj * 2) * kD + (c & 3) * 128 + warp * 16 + rr;
            st_rlx(d2, nr);
            st_rlx(d2 + kD, nr);
            st_rlx(d2 + 8, nr);
            st_rlx(d2 + kD + 8, nr);
        }
    }

    {
        float qc[4][4];
#pragma unroll
        for (int n = 0; n < 4; n++)
#pragma unroll
            for (int e = 0; e < 4; e++) qc[n][e] = 0.f;
        uint32_t a[8];
        ldsm4(x_addr + (warp * 64) * 2, a[0], a[1], a[2], a[3]);
        ldsm4(x_addr + (warp * 64 + 32) * 2, a[4], a[5], a[6], a[7]);
        mbar_wait(bar_full + st * 8, ph);
        TS(2);
#pragma unroll
        for (int ks = 0; ks < 4; ks++) {
            const int row = warp * 64 + ks * 16 + (lane & 15);
#pragma unroll
            for (int np = 0; np < 2; np++) {
                uint32_t b0, b1, b2, b3;
                const int chunk = np * 2 + (lane >> 4);
                ldsm4t(sb + OFF_RING + st * STAGE + row * 64 + ((chunk ^ ((row >> 1) & 3)) << 4), b0, b1, b2, b3);
                mma16816(qc[np * 2], a[ks * 2], 0u, a[ks * 2 + 1], 0u, b0, b1);
                mma16816(qc[np * 2 + 1], a[ks * 2], 0u, a[ks * 2 + 1], 0u, b2, b3);
            }
        }
        release();
        if (lane < 16) {
#pragma unroll
            for (int n = 0; n < 4; n++)
                *reinterpret_cast<float2*>(comb + warp * 128 + rr * 32 + n * 8 + jj * 2) = make_float2(qc[n][0], qc[n][1]);
        }
        bar_consumers();
        if (tid < 128) {
            float s = 0.f;
#pragma unroll
            for (int w = 0; w < NCW; w++) s += comb[w * 128 + tid];
            st_rlx(g_q + (tid >> 5) * (kHQ * kDH) + 32 * c + (tid & 31), tagw(s, tag));
            TS(3);
            const uint32_t* qsrc = g_q + batch * (kHQ * kDH) + hkv * 512 + tid * 4;
            uint4 v = ld_rlx4(qsrc);
            int it = 0;
            while (!tag_ok(v, tag)) {
                if (++it > (1 << 21)) __trap();
                __nanosleep(64);
                v = ld_rlx4(qsrc);
            }
            uint2 pk;
            pk.x = pack_bf16(__uint_as_float(v.x), __uint_as_float(v.y));
            pk.y = pack_bf16(__uint_as_float(v.z), __uint_as_float(v.w));
            *reinterpret_cast<uint2*>(sp + OFF_Q + ((tid >> 5) * QP + (tid & 31) * 4) * 2) = pk;
        }
        bar_consumers();
    }
    TS(4);
    uint32_t qa[8];
    {
        const uint32_t qaddr = sb + OFF_Q + ((r8 & 3) * QP + (r8 >> 2) * 64 + mi * 8) * 2;
        ldsm4(qaddr, qa[0], qa[1], qa[2], qa[3]);
        ldsm4(qaddr + 64, qa[4], qa[5], qa[6], qa[7]);
    }

    float o[4][4];
#pragma unroll
    for (int m = 0; m < 4; m++)
#pragma unroll
        for (int e = 0; e < 4; e++) o[m][e] = 0.f;
    float m_run = -INFINITY, l_run = 0.f;
    const uint32_t k_off = (warp * 32 + r8) * 128 + ((mi ^ r8) << 4);
    const uint32_t v_off = (warp * 32 + (mi >> 1) * 8 + r8) * 128 + (((mi & 1) ^ r8) << 4);
    const uint32_t pmask = lane < 16 ? 0x0000ffffu : 0xffff0000u;
    float fsum[4] = {0.f, 0.f, 0.f, 0.f};
    const int bf = c >> 5, col_f = (c & 31) * 16 + (warp & 3) * 4;

    auto scores = [&](float (&sc)[4]) {
        float s[4][4];
        const uint32_t kb = sb + OFF_RING + st * STAGE;
#pragma unroll
        for (int g = 0; g < 4; g++) {
#pragma unroll
            for (int e = 0; e < 4; e++) s[g][e] = 0.f;
            uint32_t b0, b1, b2, b3;
            ldsm4(kb + k_off + g * 1024, b0, b1, b2, b3);
            mma16816(s[g], qa[0], 0u, qa[1], 0u, b0, b1);
            mma16816(s[g], qa[2], 0u, qa[3], 0u, b2, b3);
            ldsm4(kb + (k_off ^ 64u) + g * 1024, b0, b1, b2, b3);
            mma16816(s[g], qa[4], 0u, qa[5], 0u, b0, b1);
            mma16816(s[g], qa[6], 0u, qa[7], 0u, b2, b3);
        }
        release();
#pragma unroll
        for (int g = 0; g < 4; g++) {
            const float v = lane < 16 ? s[g][0] : s[g][1];
            sc[g] = v + __shfl_xor_sync(0xffffffffu, v, 16);
        }
    };
    auto rescale = [&](float m_new) {
        const float alpha = ex2((m_run - m_new) * kScaleLog2);
        l_run *= alpha;
        const float a0 = __shfl_sync(0xffffffffu, alpha, ((2 * jj) & 3) * 4);
        const float a1 = __shfl_sync(0xffffffffu, alpha, ((2 * jj + 1) & 3) * 4);
#pragma unroll
        for (int m = 0; m < 4; m++) {
            o[m][0] *= a0; o[m][1] *= a1; o[m][2] *= a0; o[m][3] *= a1;
        }
        m_run = m_new;
    };
    auto probs = [&](const float (&sc)[4], uint32_t (&pb)[4]) {
        const float mc = m_run * kScaleLog2;
#pragma unroll
        for (int g = 0; g < 4; g++) {
            const float p = ex2(fmaf(sc[g], kScaleLog2, -mc));
            l_run += p;
            pb[g] = pack_bf16(p, p) & pmask;
        }
    };

    for (int t = 0; t < NT - 1; t++) {
        mbar_wait(bar_full + st * 8, ph);
        float sc[4];
        scores(sc);
        float mx = fmaxf(fmaxf(sc[0], sc[1]), fmaxf(sc[2], sc[3]));
        mx = fmaxf(mx, __shfl_xor_sync(0xffffffffu, mx, 1));
        mx = fmaxf(mx, __shfl_xor_sync(0xffffffffu, mx, 2));
        const float m_new = fmaxf(m_run, mx);
        if (__any_sync(0xffffffffu, m_new > m_run)) rescale(m_new);
        uint32_t pb[4];
        probs(sc, pb);
        if (t == NT - 4 && warp < 4) {
            uint4 v = make_uint4(0, 0, 0, 0);
            if (lane < NFFN) v = poll4(g_pb + ((kHQ + lane) * kB + bf) * kD + col_f, tag);
            __syncwarp();
            fsum[0] = __uint_as_float(v.x); fsum[1] = __uint_as_float(v.y);
            fsum[2] = __uint_as_float(v.z); fsum[3] = __uint_as_float(v.w);
#pragma unroll
            for (int e = 0; e < 4; e++) {
                fsum[e] += __shfl_xor_sync(0xffffffffu, fsum[e], 1);
                fsum[e] += __shfl_xor_sync(0xffffffffu, fsum[e], 2);
            }
        }
        mbar_wait(bar_full + st * 8, ph);
        {
            const uint32_t vb = sb + OFF_RING + st * STAGE;
#pragma unroll
            for (int oc = 0; oc < 2; oc++) {
#pragma unroll
                for (int m = 0; m < 4; m++) {
                    uint32_t a0, a1, a2, a3;
                    ldsm4t(vb + ((v_off + oc * 2048) ^ (m * 32)), a0, a1, a2, a3);
                    mma16816(o[m], a0, a1, a2, a3, pb[oc * 2], pb[oc * 2 + 1]);
                }
            }
        }
        release();
    }

    {
        mbar_wait(bar_full + st * 8, ph);
        TS(9);
        float sc[4];
        scores(sc);
        float mx = fmaxf(fmaxf(sc[0], sc[1]), fmaxf(sc[2], sc[3]));
        mx = fmaxf(mx, __shfl_xor_sync(0xffffffffu, mx, 1));
        mx = fmaxf(mx, __shfl_xor_sync(0xffffffffu, mx, 2));
        float m_new = fmaxf(m_run, mx);
        if (lane < 16 && jj == 0) mx_s[warp * 4 + rr] = m_new;
        bar_consumers();
#pragma unroll
        for (int w = 0; w < NCW; w++) m_new = fmaxf(m_new, mx_s[w * 4 + (rr & 3)]);
        if (__any_sync(0xffffffffu, m_new > m_run)) rescale(m_new);
        uint32_t pb[4];
        probs(sc, pb);
        l_run += __shfl_xor_sync(0xffffffffu, l_run, 1);
        l_run += __shfl_xor_sync(0xffffffffu, l_run, 2);
        if (lane < 16 && jj == 0) l_s[warp * 4 + rr] = l_run;
        uint4* pbuf = reinterpret_cast<uint4*>(sp + OFF_X);
        pbuf[tid] = make_uint4(pb[0], pb[1], pb[2], pb[3]);
        {
            float* dst = comb + warp * COMB_W + jj * 8 + rr;
#pragma unroll
            for (int m = 0; m < 4; m++)
#pragma unroll
                for (int e = 0; e < 4; e++) dst[(2 * m + (e >> 1)) * 80 + (e & 1) * 48] = o[m][e];
        }
        bar_consumers();
        if (tid < 16 && jj == 0) {
            float l = 0.f;
#pragma unroll
            for (int w = 0; w < NCW; w++) l += l_s[w * 4 + rr];
            st_rlx2(g_ml + (c * 4 + rr) * 2, tagw(m_run, tag), tagw(l, tag));
        }
        float2 prev;
        {
            const float* src = comb + warp * 80 + (rr & 1) * 48 + (rr >> 1) * 8 + jj * 2;
            prev = *reinterpret_cast<const float2*>(src);
#pragma unroll
            for (int w = 1; w < NCW; w++) {
                const float2 v = *reinterpret_cast<const float2*>(src + w * COMB_W);
                prev.x += v.x; prev.y += v.y;
            }
        }
        uint4 pf[NVP];
#pragma unroll
        for (int j = 0; j < NVP; j++) pf[j] = pbuf[j * 32 + lane];
        float acc[4][4];
#pragma unroll
        for (int u = 0; u < 4; u++)
#pragma unroll
            for (int e = 0; e < 4; e++) acc[u][e] = 0.f;
        acc[0][0] = prev.x; acc[0][1] = prev.y;
        const uint32_t vb = sb + OFF_RING + st * STAGE + lane * 128 + ((warp ^ r8) << 4);
#pragma unroll
        for (int j = 0; j < NVP; j++) {
            mbar_wait(bar_vp + j * 8, 0);
            uint32_t b0, b1, b2, b3;
            ldsm4t(vb + j * (STAGE / NVP), b0, b1, b2, b3);
            mma16816(acc[(j & 1) * 2], pf[j].x, 0u, pf[j].y, 0u, b0, b1);
            mma16816(acc[(j & 1) * 2 + 1], pf[j].z, 0u, pf[j].w, 0u, b2, b3);
        }
        TS(10);
        advance();
        st_rlx2(g_pa + (c * 4 + (rr & 3)) * kDH + (rr >> 2) * 64 + warp * 8 + jj * 2,
                tagw((acc[0][0] + acc[1][0]) + (acc[2][0] + acc[3][0]), tag),
                tagw((acc[0][1] + acc[1][1]) + (acc[2][1] + acc[3][1]), tag));
    }
    TS(11);

    uint32_t wf[8][4];
    auto load_wo = [&]() {
        const uint32_t wb = sb + OFF_RING + st * STAGE + (warp >> 2) * 16384 + ((mi >> 1) * 8 + r8) * 128 +
                            ((((warp & 3) * 2 + (mi & 1)) ^ r8) << 4);
#pragma unroll
        for (int ks = 0; ks < 8; ks++) ldsm4t(wb + ks * 2048, wf[ks][0], wf[ks][1], wf[ks][2], wf[ks][3]);
    };
    {
        const int hh = (c >> 2) & 3;
        const uint32_t* pm = g_ml + (((c & ~15) | ((warp >> 1) << 2)) * 4 + hh) * 2;
        const uint32_t* po = g_pa + (((c & ~15) | ((warp >> 1) << 2)) * 4 + hh) * kDH + (warp & 1) * 64 + lane * 2;
        uint2 v[4];
        auto load_pa = [&](uint2 (&d)[4]) {
#pragma unroll
            for (int s = 0; s < 4; s++) d[s] = ld_rlx2(po + s * (4 * kDH));
        };
        auto pa_ok = [&](const uint2 (&d)[4]) {
            return ((((d[0].x ^ tag) | (d[0].y ^ tag) | (d[1].x ^ tag) | (d[1].y ^ tag) | (d[2].x ^ tag) | (d[2].y ^ tag) |
                      (d[3].x ^ tag) | (d[3].y ^ tag)) & 1u) == 0);
        };
        spin(DLY_M);
        uint2 mlv[4];
#pragma unroll
        for (int s = 0; s < 4; s++) mlv[s] = ld_rlx2(pm + s * 8);
        int it = 0;
        while (!pa_ok(mlv)) {
            if (++it > (1 << 21)) __trap();
#pragma unroll
            for (int s = 0; s < 4; s++) mlv[s] = ld_rlx2(pm + s * 8);
        }
        TS(19);
        float w4[4];
        {
            const float ms[4] = {__uint_as_float(mlv[0].x), __uint_as_float(mlv[1].x), __uint_as_float(mlv[2].x), __uint_as_float(mlv[3].x)};
            const float ls[4] = {__uint_as_float(mlv[0].y), __uint_as_float(mlv[1].y), __uint_as_float(mlv[2].y), __uint_as_float(mlv[3].y)};
            const float M = fmaxf(fmaxf(ms[0], ms[1]), fmaxf(ms[2], ms[3]));
            float L = 0.f;
#pragma unroll
            for (int s = 0; s < 4; s++) {
                w4[s] = ex2((ms[s] - M) * kScaleLog2);
                L = fmaf(w4[s], ls[s], L);
            }
            const float inv = 1.f / L;
#pragma unroll
            for (int s = 0; s < 4; s++) w4[s] *= inv;
        }
        mbar_wait(bar_full + st * 8, ph);
        TS(20);
        load_pa(v);
        load_wo();
        while (!__all_sync(0xffffffffu, pa_ok(v))) {
            if (++it > (1 << 21)) __trap();
            load_pa(v);
        }
        TS(12);
        float z0 = 0.f, z1 = 0.f;
#pragma unroll
        for (int s = 0; s < 4; s++) {
            z0 = fmaf(w4[s], __uint_as_float(v[s].x), z0);
            z1 = fmaf(w4[s], __uint_as_float(v[s].y), z1);
        }
        *reinterpret_cast<uint32_t*>(sp + OFF_Q + ((warp >> 1) * QP + (warp & 1) * 64 + lane * 2) * 2) = pack_bf16(z0, z1);
    }
    bar_consumers();
    {
        const uint32_t oaddr = sb + OFF_Q + ((r8 & 3) * QP + mi * 8) * 2;
        float acc[4][4];
#pragma unroll
        for (int u = 0; u < 4; u++)
#pragma unroll
            for (int e = 0; e < 4; e++) acc[u][e] = 0.f;
#pragma unroll
        for (int kp = 0; kp < 4; kp++) {
            uint32_t b0, b1, b2, b3;
            ldsm4(oaddr + kp * 64, b0, b1, b2, b3);
            mma16816(acc[(kp & 1) * 2], wf[kp * 2][0], wf[kp * 2][1], wf[kp * 2][2], wf[kp * 2][3], b0, b1);
            mma16816(acc[(kp & 1) * 2 + 1], wf[kp * 2 + 1][0], wf[kp * 2 + 1][1], wf[kp * 2 + 1][2], wf[kp * 2 + 1][3], b2, b3);
        }
        if (jj < 2) {
            uint32_t* dst = g_pb + ((c >> 2) * kB + jj * 2) * kD + (c & 3) * 128 + warp * 16 + rr;
            st_rlx(dst, tagw((acc[0][0] + acc[1][0]) + (acc[2][0] + acc[3][0]), tag));
            st_rlx(dst + kD, tagw((acc[0][1] + acc[1][1]) + (acc[2][1] + acc[3][1]), tag));
            st_rlx(dst + 8, tagw((acc[0][2] + acc[1][2]) + (acc[2][2] + acc[3][2]), tag));
            st_rlx(dst + kD + 8, tagw((acc[0][3] + acc[1][3]) + (acc[2][3] + acc[3][3]), tag));
        }
    }
    TS(13);
    if (warp < 4) {
        const uint32_t* pbp = g_pb + (lane * kB + bf) * kD + col_f;
        spin(DLY_B);
        const uint4 v = poll4(pbp, tag);
        __syncwarp();
        TS(14);
        const float a[4] = {__uint_as_float(v.x), __uint_as_float(v.y), __uint_as_float(v.z), __uint_as_float(v.w)};
        const bool b0 = lane & 1, b1 = lane & 2;
        const float s0 = b0 ? a[0] : a[1], k0 = b0 ? a[1] : a[0];
        const float s1 = b0 ? a[2] : a[3], k1 = b0 ? a[3] : a[2];
        const float r0 = k0 + __shfl_xor_sync(0xffffffffu, s0, 1);
        const float r1 = k1 + __shfl_xor_sync(0xffffffffu, s1, 1);
        float r = (b1 ? r1 : r0) + __shfl_xor_sync(0xffffffffu, b1 ? r0 : r1, 2);
        r += __shfl_xor_sync(0xffffffffu, r, 4);
        r += __shfl_xor_sync(0xffffffffu, r, 8);
        r += __shfl_xor_sync(0xffffffffu, r, 16);
        if (lane < 4) {
            const float g = misc_f[0];
            const float f = b1 ? (b0 ? fsum[3] : fsum[2]) : (b0 ? fsum[1] : fsum[0]);
            prm.out[bf * kD + col_f + lane] = __float2bfloat16_rn(g * r + (1.f - g) * f);
            if (c == 0 && warp == 0 && lane == 0) {
                asm volatile("st.relaxed.gpu.global.u32 [%0], %1;" ::"l"(&g_epoch), "r"(epoch + 1u) : "memory");
            }
        }
        TS(15);
    }
}

typedef CUresult (*EncodeFn)(CUtensorMap*, CUtensorMapDataType, cuuint32_t, void*, const cuuint64_t*, const cuuint64_t*,
                             const cuuint32_t*, const cuuint32_t*, CUtensorMapInterleave, CUtensorMapSwizzle,
                             CUtensorMapL2promotion, CUtensorMapFloatOOBfill);

void encode2d(EncodeFn enc, CUtensorMap* m, const void* base, uint64_t cols, uint64_t rows, uint64_t pitch_bytes,
              uint32_t box_cols, uint32_t box_rows, CUtensorMapSwizzle swz) {
    cuuint64_t gd[2] = {cols, rows};
    cuuint64_t gs[1] = {pitch_bytes};
    cuuint32_t bd[2] = {box_cols, box_rows};
    cuuint32_t es[2] = {1, 1};
    enc(m, CU_TENSOR_MAP_DATA_TYPE_BFLOAT16, 2, const_cast<void*>(base), gd, gs, bd, es, CU_TENSOR_MAP_INTERLEAVE_NONE,
        swz, CU_TENSOR_MAP_L2_PROMOTION_L2_128B, CU_TENSOR_MAP_FLOAT_OOB_FILL_NONE);
}

}

extern "C" void kernel_launch(void* const* d_in, const int* in_sizes, int n_in, void* d_out, int out_size) {
    (void)in_sizes; (void)n_in; (void)out_size;
    static EncodeFn enc = nullptr;
    if (!enc) {
        void* fn = nullptr;
        cudaDriverEntryPointQueryResult qr;
        cudaGetDriverEntryPoint("cuTensorMapEncodeTiled", &fn, cudaEnableDefault, &qr);
        enc = reinterpret_cast<EncodeFn>(fn);
        cudaFuncSetAttribute(fused_decode_kernel, cudaFuncAttributeMaxDynamicSharedMemorySize, SMEM_BYTES);
    }
    CUtensorMap tk, tv, tvp, twq, two, twg, twu, twd;
    encode2d(enc, &tk, d_in[1], 64, (uint64_t)kB * kHKV * kSK * 2, 128, 64, 256, CU_TENSOR_MAP_SWIZZLE_128B);
    encode2d(enc, &tv, d_in[2], 64, (uint64_t)kB * kHKV * kSK * 2, 128, 64, 256, CU_TENSOR_MAP_SWIZZLE_128B);
    encode2d(enc, &tvp, d_in[2], 64, (uint64_t)kB * kHKV * kSK * 2, 128, 64, 256 / NVP, CU_TENSOR_MAP_SWIZZLE_128B);
    encode2d(enc, &twq, d_in[3], kHQ * kDH, kD, kHQ * kDH * 2, 32, 256, CU_TENSOR_MAP_SWIZZLE_64B);
    encode2d(enc, &two, d_in[4], kD, kHQ * kDH, kD * 2, 64, 128, CU_TENSOR_MAP_SWIZZLE_128B);
    encode2d(enc, &twg, d_in[6], kF, kD, kF * 2, 64, 256, CU_TENSOR_MAP_SWIZZLE_128B);
    encode2d(enc, &twu, d_in[7], kF, kD, kF * 2, 64, 256, CU_TENSOR_MAP_SWIZZLE_128B);
    encode2d(enc, &twd, d_in[8], kD, kF, kD * 2, 64, 64, CU_TENSOR_MAP_SWIZZLE_128B);
    Params prm;
    prm.x = reinterpret_cast<const __nv_bfloat16*>(d_in[0]);
    prm.gate_w = reinterpret_cast<const __nv_bfloat16*>(d_in[9]);
    prm.out = reinterpret_cast<__nv_bfloat16*>(d_out);
    fused_decode_kernel<<<NCTA, NTHREADS, SMEM_BYTES>>>(tk, tv, tvp, twq, two, twg, twu, twd, prm);
}
```

```cpp
#include <cuda_runtime.h>
#include <cuda_bf16.h>
#include <cuda.h>
#include <stdint.h>

#define EVICT_FIRST 1
#define WIN 2
#define INIT_WRITES 1
#define PACE 1
#define PACE_K 16
#define PACE_L0 (-32)
#define PACE_MAX 2000
#define WO_AT 7
#define DLY_M 650
#define DLY_B 250

namespace {

constexpr int kB = 4, kD = 512, kHQ = 32, kHKV = 8, kDH = 128, kSK = 16384, kF = 1792;
constexpr int NATT = 128;
constexpr int NFFN = 4;
constexpr int NCTA = NATT + NFFN;
constexpr int NSTAGE = 6;
constexpr int STAGE = 32768;
constexpr int NCW = 8;
constexpr int NTHREADS = (NCW + 1) * 32;
constexpr int KEYS_PER_CTA = kSK / 4;
constexpr int NT = KEYS_PER_CTA / 128;
constexpr int ATT_STAGES = 2 + 2 * NT;
constexpr int FCOLS = kF / NFFN;
constexpr int FBLK = FCOLS / 64;
constexpr int FFN_STAGES = 4 * FBLK + 2 * FBLK;

constexpr int XP = 520;
constexpr int QP = 136;
constexpr int HP = FCOLS + 8;
constexpr int COMB_W = 640;
constexpr int OFF_RING = 0;
constexpr int OFF_COMB = NSTAGE * STAGE;
constexpr int OFF_X = OFF_COMB + NCW * COMB_W * 4;
constexpr int OFF_Q = OFF_X + kB * XP * 2;
constexpr int OFF_H = OFF_Q + kB * QP * 2;
constexpr int OFF_MX = OFF_H + kB * HP * 2;
constexpr int OFF_L = OFF_MX + NCW * 4 * 4;
constexpr int OFF_MISC = OFF_L + NCW * 4 * 4;
constexpr int OFF_BAR = OFF_MISC + 16;
constexpr int NVP = 8;
constexpr int SMEM_USED = OFF_BAR + (2 * NSTAGE + NVP) * 8;
constexpr int SMEM_BYTES = SMEM_USED + 1024;
static_assert(SMEM_BYTES <= 232448, "smem");
static_assert(OFF_X % 16 == 0 && OFF_Q % 16 == 0 && OFF_H % 16 == 0 && OFF_BAR % 8 == 0, "align");

constexpr float kScaleLog2 = 0.08838834764831845f * 1.4426950408889634f;

__device__ uint32_t g_epoch;
__device__ __align__(128) uint32_t g_prog[2 * 32];
__device__ __align__(128) uint32_t g_q[kB * kHQ * kDH];
__device__ __align__(128) uint32_t g_pa[NATT * 4 * kDH];
__device__ __align__(128) uint32_t g_ml[NATT * 4 * 2];
__device__ __align__(128) uint32_t g_pb[(kHQ + NFFN) * kB * kD];

#define TS(i)
#define TSP(i)

__device__ __forceinline__ uint32_t smem_u32(const void* p) { return (uint32_t)__cvta_generic_to_shared(p); }
__device__ __forceinline__ void mbar_init(uint32_t bar, uint32_t cnt) {
    asm volatile("mbarrier.init.shared::cta.b64 [%0], %1;" ::"r"(bar), "r"(cnt));
}
__device__ __forceinline__ void mbar_expect_tx(uint32_t bar, uint32_t bytes) {
    asm volatile("mbarrier.arrive.expect_tx.shared::cta.b64 _, [%0], %1;" ::"r"(bar), "r"(bytes) : "memory");
}
__device__ __forceinline__ void mbar_arrive(uint32_t bar) {
    asm volatile("mbarrier.arrive.shared::cta.b64 _, [%0];" ::"r"(bar) : "memory");
}
__device__ __forceinline__ bool mbar_try_wait(uint32_t bar, uint32_t parity) {
    uint32_t ok;
    asm volatile("{\n.reg .pred p;\nmbarrier.try_wait.parity.shared::cta.b64 p, [%1], %2;\nselp.u32 %0, 1, 0, p;\n}"
                 : "=r"(ok) : "r"(bar), "r"(parity) : "memory");
    return ok;
}
__device__ __forceinline__ void mbar_wait(uint32_t bar, uint32_t parity) {
    if (mbar_try_wait(bar, parity)) return;
    const long long t0 = clock64();
    while (!mbar_try_wait(bar, parity)) {
        if (clock64() - t0 > 4000000000LL) __trap();
    }
}
__device__ __forceinline__ void tma2d(uint32_t dst, const CUtensorMap* m, int c0, int c1, uint32_t bar) {
    asm volatile("cp.async.bulk.tensor.2d.shared::cluster.global.mbarrier::complete_tx::bytes [%0], [%1, {%3, %4}], [%2];"
                 ::"r"(dst), "l"(m), "r"(bar), "r"(c0), "r"(c1) : "memory");
}
__device__ __forceinline__ void tma2d_hint(uint32_t dst, const CUtensorMap* m, int c0, int c1, uint32_t bar, uint64_t pol) {
    asm volatile("cp.async.bulk.tensor.2d.shared::cluster.global.mbarrier::complete_tx::bytes.L2::cache_hint"
                 " [%0], [%1, {%3, %4}], [%2], %5;"
                 ::"r"(dst), "l"(m), "r"(bar), "r"(c0), "r"(c1), "l"(pol) : "memory");
}
__device__ __forceinline__ void prefetch_tmap(const CUtensorMap* m) {
    asm volatile("prefetch.tensormap [%0];" ::"l"(m) : "memory");
}
__device__ __forceinline__ void ldsm4(uint32_t addr, uint32_t& r0, uint32_t& r1, uint32_t& r2, uint32_t& r3) {
    asm volatile("ldmatrix.sync.aligned.m8n8.x4.shared.b16 {%0,%1,%2,%3}, [%4];"
                 : "=r"(r0), "=r"(r1), "=r"(r2), "=r"(r3) : "r"(addr) : "memory");
}
__device__ __forceinline__ void ldsm4t(uint32_t addr, uint32_t& r0, uint32_t& r1, uint32_t& r2, uint32_t& r3) {
    asm volatile("ldmatrix.sync.aligned.m8n8.x4.trans.shared.b16 {%0,%1,%2,%3}, [%4];"
                 : "=r"(r0), "=r"(r1), "=r"(r2), "=r"(r3) : "r"(addr) : "memory");
}
__device__ __forceinline__ void mma16816(float (&c)[4], uint32_t a0, uint32_t a1, uint32_t a2, uint32_t a3,
                                         uint32_t b0, uint32_t b1) {
    asm volatile("mma.sync.aligned.m16n8k16.row.col.f32.bf16.bf16.f32 {%0,%1,%2,%3}, {%4,%5,%6,%7}, {%8,%9}, {%0,%1,%2,%3};"
                 : "+f"(c[0]), "+f"(c[1]), "+f"(c[2]), "+f"(c[3])
                 : "r"(a0), "r"(a1), "r"(a2), "r"(a3), "r"(b0), "r"(b1));
}
__device__ __forceinline__ float ex2(float x) {
    float y;
    asm("ex2.approx.ftz.f32 %0, %1;" : "=f"(y) : "f"(x));
    return y;
}
__device__ __forceinline__ uint32_t pack_bf16(float lo, float hi) {
    uint32_t r;
    asm("cvt.rn.bf16x2.f32 %0, %1, %2;" : "=r"(r) : "f"(hi), "f"(lo));
    return r;
}
__device__ __forceinline__ float bf16_round(float v) { return __bfloat162float(__float2bfloat16_rn(v)); }
__device__ __forceinline__ void spin(int cycles) {
    const uint32_t t0 = clock();
    while ((int)(clock() - t0) < cycles) {}
}
__device__ __forceinline__ void bar_consumers() { asm volatile("bar.sync 1, 256;" ::: "memory"); }

__device__ __forceinline__ uint32_t tagw(float v, uint32_t tag) { return (__float_as_uint(v) & ~1u) | tag; }
__device__ __forceinline__ void st_rlx(uint32_t* p, uint32_t v) {
    asm volatile("st.relaxed.gpu.global.u32 [%0], %1;" ::"l"(p), "r"(v) : "memory");
}
__device__ __forceinline__ void st_rlx2(uint32_t* p, uint32_t a, uint32_t b) {
    asm volatile("st.relaxed.gpu.global.v2.u32 [%0], {%1,%2};" ::"l"(p), "r"(a), "r"(b) : "memory");
}
__device__ __forceinline__ uint4 ld_rlx4(const uint32_t* p) {
    uint4 v;
    asm volatile("ld.relaxed.gpu.global.v4.u32 {%0,%1,%2,%3}, [%4];"
                 : "=r"(v.x), "=r"(v.y), "=r"(v.z), "=r"(v.w) : "l"(p) : "memory");
    return v;
}
__device__ __forceinline__ uint2 ld_rlx2(const uint32_t* p) {
    uint2 v;
    asm volatile("ld.relaxed.gpu.global.v2.u32 {%0,%1}, [%2];" : "=r"(v.x), "=r"(v.y) : "l"(p) : "memory");
    return v;
}
__device__ __forceinline__ bool tag_ok(uint4 v, uint32_t tag) {
    return (((v.x ^ tag) | (v.y ^ tag) | (v.z ^ tag) | (v.w ^ tag)) & 1u) == 0;
}
__device__ __forceinline__ uint4 poll4(const uint32_t* p, uint32_t tag) {
    uint4 v = ld_rlx4(p);
    int it = 0;
    while (!tag_ok(v, tag)) {
        if (++it > (1 << 21)) __trap();
        v = ld_rlx4(p);
    }
    return v;
}

__device__ __forceinline__ int tile_line(int c, int t) {
    return (((c >> 2) & 3) * kHKV + (c >> 4)) * (kSK * 2) + (t * 4 + (c & 3)) * 256;
}

struct Params {
    const __nv_bfloat16* x;
    const __nv_bfloat16* gate_w;
    __nv_bfloat16* out;
};

__global__ void __launch_bounds__(NTHREADS, 1)
fused_decode_kernel(const __grid_constant__ CUtensorMap tm_k, const __grid_constant__ CUtensorMap tm_v,
                    const __grid_constant__ CUtensorMap tm_vp,
                    const __grid_constant__ CUtensorMap tm_wq, const __grid_constant__ CUtensorMap tm_wo,
                    const __grid_constant__ CUtensorMap tm_wg, const __grid_constant__ CUtensorMap tm_wu,
                    const __grid_constant__ CUtensorMap tm_wd, const Params prm) {
    extern __shared__ uint8_t smem_raw[];
    const uint32_t sraw = smem_u32(smem_raw);
    uint32_t sb = (sraw + 1023u) & ~1023u;
    uint64_t p_wq = reinterpret_cast<uint64_t>(&tm_wq), p_k = reinterpret_cast<uint64_t>(&tm_k);
    asm volatile("" : "+r"(sb), "+l"(p_wq), "+l"(p_k));
    uint8_t* sp = smem_raw + (((sraw + 1023u) & ~1023u) - sraw);
    const int tid = threadIdx.x, warp = tid >> 5, lane = tid & 31;
    const int c = blockIdx.x;
    const bool is_ffn = c >= NATT;
    const uint32_t bar_full = sb + OFF_BAR, bar_empty = bar_full + NSTAGE * 8, bar_vp = bar_empty + NSTAGE * 8;

    TS(0);
    if (warp == NCW) {
        uint64_t pol0;
        asm volatile("createpolicy.fractional.L2::evict_first.b64 %0, 1.0;" : "=l"(pol0));
        if (lane == 0) {
            for (int s = 0; s < WIN; s++) mbar_init(bar_full + s * 8, 1);
            asm volatile("fence.proxy.async.shared::cta;" ::: "memory");
            if (!is_ffn) {
                static_assert(WIN == 2, "the prologue issues stage 0 (wq) and stage 1 (first K tile)");
                const int l0 = tile_line(c, 0);
                mbar_expect_tx(bar_full, STAGE);
                tma2d(sb + OFF_RING, reinterpret_cast<const CUtensorMap*>(p_wq), 32 * c, 0, bar_full);
                tma2d(sb + OFF_RING + STAGE / 2, reinterpret_cast<const CUtensorMap*>(p_wq), 32 * c, 256, bar_full);
                mbar_expect_tx(bar_full + 8, STAGE);
                tma2d_hint(sb + OFF_RING + STAGE, reinterpret_cast<const CUtensorMap*>(p_k), 0, l0, bar_full + 8, pol0);
            }
        }
        const int nst = is_ffn ? FFN_STAGES : ATT_STAGES;
        const int f0 = (c - NATT) * FCOLS;
        uint64_t pol;
        asm volatile("createpolicy.fractional.L2::evict_first.b64 %0, 1.0;" : "=l"(pol));
        auto issue = [&](int i, int s) {
            const uint32_t bar = bar_full + s * 8, dst = sb + OFF_RING + s * STAGE;
            if (!is_ffn && i == 2 * NT) {
#pragma unroll 1
                for (int j = 0; j < NVP; j++) {
                    mbar_expect_tx(bar_vp + j * 8, STAGE / NVP);
                    tma2d_hint(dst + j * (STAGE / NVP), &tm_vp, 0, tile_line(c, NT - 1) + j * (256 / NVP), bar_vp + j * 8, pol);
                }
                return;
            }
            mbar_expect_tx(bar, STAGE);
            if (!is_ffn) {
                if (i == 0) {
                    tma2d(dst, &tm_wq, 32 * c, 0, bar);
                    tma2d(dst + STAGE / 2, &tm_wq, 32 * c, 256, bar);
                } else if (i <= 2 * NT) {
                    const int t = (i - 1) >> 1;
                    tma2d_hint(dst, ((i - 1) & 1) ? &tm_v : &tm_k, 0, tile_line(c, t), bar, pol);
                } else {
                    tma2d(dst, &tm_wo, 128 * (c & 3), 128 * (c >> 2), bar);
                    tma2d(dst + STAGE / 2, &tm_wo, 128 * (c & 3) + 64, 128 * (c >> 2), bar);
                }
            } else {
                if (i < 4 * FBLK) {
                    tma2d(dst, (i & 2) ? &tm_wu : &tm_wg, f0 + 64 * (i >> 2), 256 * (i & 1), bar);
                } else {
                    const int ii = i - 4 * FBLK;
#pragma unroll
                    for (int blk = 0; blk < 4; blk++)
                        tma2d(dst + blk * 8192, &tm_wd, 256 * (ii & 1) + 64 * blk, f0 + 64 * (ii >> 1), bar);
                }
            }
        };
        if (lane == 0) {
            TSP(16);
            if (is_ffn) for (int s = 0; s < WIN; s++) issue(s, s);
            TSP(17);
            for (int s = 0; s < NSTAGE; s++) {
                if (s >= WIN) mbar_init(bar_full + s * 8, 1);
                mbar_init(bar_empty + s * 8, NCW);
            }
            for (int s = 0; s < NVP; s++) mbar_init(bar_vp + s * 8, 1);
            asm volatile("fence.mbarrier_init.release.cluster;" ::: "memory");
            asm volatile("fence.proxy.async.shared::cta;" ::: "memory");
        }
        __syncthreads();
        if (lane == 0) {
            int s = WIN % NSTAGE, sw = 0;
            uint32_t ph = WIN == NSTAGE ? 0 : 1, phw = 0;
            const uint32_t ep = *reinterpret_cast<volatile uint32_t*>(sp + OFF_MISC + 4);
            uint32_t* prog = g_prog + (ep & 1u) * 32;
            if (c == 0) st_rlx(g_prog + ((ep + 1u) & 1u) * 32, 0u);
            uint32_t r_old = 0;
            int dly = 0;
            for (int i = WIN; i < nst; i++) {
                mbar_wait(bar_full + sw * 8, phw);
                const uint32_t t0 = clock();
                if (!is_ffn && (i & 1)) {
                    if (i >= 5) dly = min(max((64 * (i - 3) - (int)r_old - 1 - (PACE_L0)) * PACE_K, 0), PACE_MAX);
                    asm volatile("atom.relaxed.gpu.global.add.u32 %0, [%1], 1;" : "=r"(r_old) : "l"(prog) : "memory");
                }
                if (i >= NSTAGE) mbar_wait(bar_empty + s * 8, ph);
                if (WO_AT >= 0 && !is_ffn && i == ATT_STAGES - 1) {
                    mbar_wait(bar_vp + (WO_AT < 0 ? 0 : WO_AT) * 8, 0);
                }
                while ((int)(clock() - t0) < dly) {}
                issue(i, s);
                if (++s == NSTAGE) { s = 0; ph ^= 1; }
                if (++sw == NSTAGE) { sw = 0; phw ^= 1; }
            }
            TSP(18);
        }
        return;
    }

    {
        const uint4 xv = __ldg(reinterpret_cast<const uint4*>(prm.x) + tid);
        *reinterpret_cast<uint4*>(sp + OFF_X + ((tid >> 6) * XP + (tid & 63) * 8) * 2) = xv;
    }
    float* misc_f = reinterpret_cast<float*>(sp + OFF_MISC);
    uint32_t* misc_u = reinterpret_cast<uint32_t*>(sp + OFF_MISC);
    if (tid == 0) {
        uint32_t e;
        asm volatile("ld.relaxed.gpu.global.u32 %0, [%1];" : "=r"(e) : "l"(&g_epoch) : "memory");
        misc_u[1] = e;
    }
    if (warp == NCW - 1 && !is_ffn) {
        const int bf = c >> 5;
        const uint4* xp = reinterpret_cast<const uint4*>(prm.x + bf * kD) + lane * 2;
        const uint4* gp = reinterpret_cast<const uint4*>(prm.gate_w) + lane * 2;
        float acc = 0.f;
#pragma unroll
        for (int u = 0; u < 2; u++) {
            const uint4 a = __ldg(xp + u), g = __ldg(gp + u);
            const uint32_t aw[4] = {a.x, a.y, a.z, a.w}, gw[4] = {g.x, g.y, g.z, g.w};
#pragma unroll
            for (int e = 0; e < 4; e++) {
                acc = fmaf(__uint_as_float(aw[e] << 16), __uint_as_float(gw[e] << 16), acc);
                acc = fmaf(__uint_as_float(aw[e] & 0xffff0000u), __uint_as_float(gw[e] & 0xffff0000u), acc);
            }
        }
#pragma unroll
        for (int o = 16; o > 0; o >>= 1) acc += __shfl_xor_sync(0xffffffffu, acc, o);
        if (lane == 0) misc_f[0] = 1.f / (1.f + __expf(-acc));
    }
    __syncthreads();
    TS(1);
    const uint32_t epoch = misc_u[1];
    const uint32_t tag = (epoch + 1u) & 1u;

    const int r8 = lane & 7, mi = lane >> 3;
    const int rr = lane >> 2, jj = lane & 3;
    int st = 0;
    uint32_t ph = 0;
    auto advance = [&]() { if (++st == NSTAGE) { st = 0; ph ^= 1; } };
    auto release = [&]() {
        __syncwarp();
        if (lane == 0) mbar_arrive(bar_empty + st * 8);
        advance();
    };
    const uint32_t x_addr = sb + OFF_X + ((r8 & 3) * XP + mi * 8) * 2;

    if (is_ffn) {
        const int fi = c - NATT;
        if (lane < 16) {
            uint32_t* dst = g_pb + ((kHQ + fi) * kB + rr) * kD + (warp >> 1) * 64 + (warp & 1) * 32 + jj * 2;
#pragma unroll
            for (int ch = 0; ch < 2; ch++)
#pragma unroll
                for (int n = 0; n < 4; n++) st_rlx2(dst + ch * 256 + n * 8, tag ^ 1u, tag ^ 1u);
        }
        for (int jb = 0; jb < FBLK; jb++) {
            float gu[2][2][4];
#pragma unroll
            for (int m = 0; m < 2; m++) {
#pragma unroll
                for (int e = 0; e < 4; e++) gu[m][0][e] = gu[m][1][e] = 0.f;
#pragma unroll
                for (int kh = 0; kh < 2; kh++) {
                    mbar_wait(bar_full + st * 8, ph);
                    const uint32_t wb = sb + OFF_RING + st * STAGE + lane * 128 + ((warp ^ r8) << 4);
#pragma unroll
                    for (int kk = 0; kk < 8; kk++) {
                        uint32_t b0, b1, b2, b3, a0, a1, a2, a3;
                        ldsm4t(wb + kk * 4096, b0, b1, b2, b3);
                        ldsm4(x_addr + (kh * 256 + kk * 32) * 2, a0, a1, a2, a3);
                        mma16816(gu[m][0], a0, 0u, a1, 0u, b0, b1);
                        mma16816(gu[m][1], a2, 0u, a3, 0u, b2, b3);
                    }
                    release();
                }
            }
            const float g0 = bf16_round(gu[0][0][0] + gu[0][1][0]), g1 = bf16_round(gu[0][0][1] + gu[0][1][1]);
            const float u0 = bf16_round(gu[1][0][0] + gu[1][1][0]), u1 = bf16_round(gu[1][0][1] + gu[1][1][1]);
            const float h0 = (g0 > 0.f ? g0 : 0.f) * u0, h1 = (g1 > 0.f ? g1 : 0.f) * u1;
            if (lane < 16)
                *reinterpret_cast<uint32_t*>(sp + OFF_H + (rr * HP + jb * 64 + warp * 8 + jj * 2) * 2) = pack_bf16(h0, h1);
        }
        bar_consumers();
        TS(10);
        float acc[2][4][4];
#pragma unroll
        for (int ch = 0; ch < 2; ch++)
#pragma unroll
            for (int n = 0; n < 4; n++)
#pragma unroll
                for (int e = 0; e < 4; e++) acc[ch][n][e] = 0.f;
        const uint32_t h_addr = sb + OFF_H + ((r8 & 3) * HP + mi * 8) * 2;
        for (int jb = 0; jb < FBLK; jb++) {
            uint32_t a[8];
            ldsm4(h_addr + (jb * 64) * 2, a[0], a[1], a[2], a[3]);
            ldsm4(h_addr + (jb * 64 + 32) * 2, a[4], a[5], a[6], a[7]);
#pragma unroll
            for (int ch = 0; ch < 2; ch++) {
                mbar_wait(bar_full + st * 8, ph);
                const uint32_t wb = sb + OFF_RING + st * STAGE + (warp >> 1) * 8192 + (lane & 15) * 128;
#pragma unroll
                for (int ks = 0; ks < 4; ks++) {
#pragma unroll
                    for (int np = 0; np < 2; np++) {
                        uint32_t b0, b1, b2, b3;
                        const int chunk = (warp & 1) * 4 + np * 2 + (lane >> 4);
                        ldsm4t(wb + ks * 2048 + ((chunk ^ r8) << 4), b0, b1, b2, b3);
                        mma16816(acc[ch][np * 2], a[ks * 2], 0u, a[ks * 2 + 1], 0u, b0, b1);
                        mma16816(acc[ch][np * 2 + 1], a[ks * 2], 0u, a[ks * 2 + 1], 0u, b2, b3);
                    }
                }
                release();
            }
        }
        if (lane < 16) {
            uint32_t* dst = g_pb + ((kHQ + fi) * kB + rr) * kD + (warp >> 1) * 64 + (warp & 1) * 32 + jj * 2;
#pragma unroll
            for (int ch = 0; ch < 2; ch++)
#pragma unroll
                for (int n = 0; n < 4; n++)
                    st_rlx2(dst + ch * 256 + n * 8, tagw(acc[ch][n][0], tag), tagw(acc[ch][n][1], tag));
        }
        TS(15);
        return;
    }

    float* comb = reinterpret_cast<float*>(sp + OFF_COMB);
    float* mx_s = reinterpret_cast<float*>(sp + OFF_MX);
    float* l_s = reinterpret_cast<float*>(sp + OFF_L);
    const int hkv = c >> 4, batch = (c >> 2) & 3;
    {
        const uint32_t nr = tag ^ 1u;
        if (tid < 128) st_rlx(g_q + (tid >> 5) * (kHQ * kDH) + 32 * c + (tid & 31), nr);
        st_rlx2(g_pa + (c * 4 + (rr & 3)) * kDH + (rr >> 2) * 64 + warp * 8 + jj * 2, nr, nr);
        if (tid < 16 && jj == 0) st_rlx2(g_ml + (c * 4 + rr) * 2, nr, nr);
        if (jj < 2) {
            uint32_t* d2 = g_pb + ((c >> 2) * kB + jj * 2) * kD + (c & 3) * 128 + warp * 16 + rr;
            st_rlx(d2, nr);
            st_rlx(d2 + kD, nr);
            st_rlx(d2 + 8, nr);
            st_rlx(d2 + kD + 8, nr);
        }
    }

    {
        float qc[4][4];
#pragma unroll
        for (int n = 0; n < 4; n++)
#pragma unroll
            for (int e = 0; e < 4; e++) qc[n][e] = 0.f;
        uint32_t a[8];
        ldsm4(x_addr + (warp * 64) * 2, a[0], a[1], a[2], a[3]);
        ldsm4(x_addr + (warp * 64 + 32) * 2, a[4], a[5], a[6], a[7]);
        mbar_wait(bar_full + st * 8, ph);
        TS(2);
#pragma unroll
        for (int ks = 0; ks < 4; ks++) {
            const int row = warp * 64 + ks * 16 + (lane & 15);
#pragma unroll
            for (int np = 0; np < 2; np++) {
                uint32_t b0, b1, b2, b3;
                const int chunk = np * 2 + (lane >> 4);
                ldsm4t(sb + OFF_RING + st * STAGE + row * 64 + ((chunk ^ ((row >> 1) & 3)) << 4), b0, b1, b2, b3);
                mma16816(qc[np * 2], a[ks * 2], 0u, a[ks * 2 + 1], 0u, b0, b1);
                mma16816(qc[np * 2 + 1], a[ks * 2], 0u, a[ks * 2 + 1], 0u, b2, b3);
            }
        }
        release();
        if (lane < 16) {
#pragma unroll
            for (int n = 0; n < 4; n++)
                *reinterpret_cast<float2*>(comb + warp * 128 + rr * 32 + n * 8 + jj * 2) = make_float2(qc[n][0], qc[n][1]);
        }
        bar_consumers();
        if (tid < 128) {
            float s = 0.f;
#pragma unroll
            for (int w = 0; w < NCW; w++) s += comb[w * 128 + tid];
            st_rlx(g_q + (tid >> 5) * (kHQ * kDH) + 32 * c + (tid & 31), tagw(s, tag));
            TS(3);
            const uint32_t* qsrc = g_q + batch * (kHQ * kDH) + hkv * 512 + tid * 4;
            uint4 v = ld_rlx4(qsrc);
            int it = 0;
            while (!tag_ok(v, tag)) {
                if (++it > (1 << 21)) __trap();
                __nanosleep(64);
                v = ld_rlx4(qsrc);
            }
            uint2 pk;
            pk.x = pack_bf16(__uint_as_float(v.x), __uint_as_float(v.y));
            pk.y = pack_bf16(__uint_as_float(v.z), __uint_as_float(v.w));
            *reinterpret_cast<uint2*>(sp + OFF_Q + ((tid >> 5) * QP + (tid & 31) * 4) * 2) = pk;
        }
        bar_consumers();
    }
    TS(4);
    uint32_t qa[8];
    {
        const uint32_t qaddr = sb + OFF_Q + ((r8 & 3) * QP + (r8 >> 2) * 64 + mi * 8) * 2;
        ldsm4(qaddr, qa[0], qa[1], qa[2], qa[3]);
        ldsm4(qaddr + 64, qa[4], qa[5], qa[6], qa[7]);
    }

    float o[4][4];
#pragma unroll
    for (int m = 0; m < 4; m++)
#pragma unroll
        for (int e = 0; e < 4; e++) o[m][e] = 0.f;
    float m_run = -INFINITY, l_run = 0.f;
    const uint32_t k_off = (warp * 32 + r8) * 128 + ((mi ^ r8) << 4);
    const uint32_t v_off = (warp * 32 + (mi >> 1) * 8 + r8) * 128 + (((mi & 1) ^ r8) << 4);
    const uint32_t pmask = lane < 16 ? 0x0000ffffu : 0xffff0000u;
    float fsum[4] = {0.f, 0.f, 0.f, 0.f};
    const int bf = c >> 5, col_f = (c & 31) * 16 + (warp & 3) * 4;

    auto scores = [&](float (&sc)[4]) {
        float s[4][4];
        const uint32_t kb = sb + OFF_RING + st * STAGE;
#pragma unroll
        for (int g = 0; g < 4; g++) {
#pragma unroll
            for (int e = 0; e < 4; e++) s[g][e] = 0.f;
            uint32_t b0, b1, b2, b3;
            ldsm4(kb + k_off + g * 1024, b0, b1, b2, b3);
            mma16816(s[g], qa[0], 0u, qa[1], 0u, b0, b1);
            mma16816(s[g], qa[2], 0u, qa[3], 0u, b2, b3);
            ldsm4(kb + (k_off ^ 64u) + g * 1024, b0, b1, b2, b3);
            mma16816(s[g], qa[4], 0u, qa[5], 0u, b0, b1);
            mma16816(s[g], qa[6], 0u, qa[7], 0u, b2, b3);
        }
        release();
#pragma unroll
        for (int g = 0; g < 4; g++) {
            const float v = lane < 16 ? s[g][0] : s[g][1];
            sc[g] = v + __shfl_xor_sync(0xffffffffu, v, 16);
        }
    };
    auto rescale = [&](float m_new) {
        const float alpha = ex2((m_run - m_new) * kScaleLog2);
        l_run *= alpha;
        const float a0 = __shfl_sync(0xffffffffu, alpha, ((2 * jj) & 3) * 4);
        const float a1 = __shfl_sync(0xffffffffu, alpha, ((2 * jj + 1) & 3) * 4);
#pragma unroll
        for (int m = 0; m < 4; m++) {
            o[m][0] *= a0; o[m][1] *= a1; o[m][2] *= a0; o[m][3] *= a1;
        }
        m_run = m_new;
    };
    auto probs = [&](const float (&sc)[4], uint32_t (&pb)[4]) {
        const float mc = m_run * kScaleLog2;
#pragma unroll
        for (int g = 0; g < 4; g++) {
            const float p = ex2(fmaf(sc[g], kScaleLog2, -mc));
            l_run += p;
            pb[g] = pack_bf16(p, p) & pmask;
        }
    };

    for (int t = 0; t < NT - 1; t++) {
        mbar_wait(bar_full + st * 8, ph);
        float sc[4];
        scores(sc);
        float mx = fmaxf(fmaxf(sc[0], sc[1]), fmaxf(sc[2], sc[3]));
        mx = fmaxf(mx, __shfl_xor_sync(0xffffffffu, mx, 1));
        mx = fmaxf(mx, __shfl_xor_sync(0xffffffffu, mx, 2));
        const float m_new = fmaxf(m_run, mx);
        if (__any_sync(0xffffffffu, m_new > m_run)) rescale(m_new);
        uint32_t pb[4];
        probs(sc, pb);
        if (t == NT - 4 && warp < 4) {
            uint4 v = make_uint4(0, 0, 0, 0);
            if (lane < NFFN) v = poll4(g_pb + ((kHQ + lane) * kB + bf) * kD + col_f, tag);
            __syncwarp();
            fsum[0] = __uint_as_float(v.x); fsum[1] = __uint_as_float(v.y);
            fsum[2] = __uint_as_float(v.z); fsum[3] = __uint_as_float(v.w);
#pragma unroll
            for (int e = 0; e < 4; e++) {
                fsum[e] += __shfl_xor_sync(0xffffffffu, fsum[e], 1);
                fsum[e] += __shfl_xor_sync(0xffffffffu, fsum[e], 2);
            }
        }
        mbar_wait(bar_full + st * 8, ph);
        {
            const uint32_t vb = sb + OFF_RING + st * STAGE;
#pragma unroll
            for (int oc = 0; oc < 2; oc++) {
#pragma unroll
                for (int m = 0; m < 4; m++) {
                    uint32_t a0, a1, a2, a3;
                    ldsm4t(vb + ((v_off + oc * 2048) ^ (m * 32)), a0, a1, a2, a3);
                    mma16816(o[m], a0, a1, a2, a3, pb[oc * 2], pb[oc * 2 + 1]);
                }
            }
        }
        release();
    }

    {
        mbar_wait(bar_full + st * 8, ph);
        TS(9);
        float sc[4];
        scores(sc);
        float mx = fmaxf(fmaxf(sc[0], sc[1]), fmaxf(sc[2], sc[3]));
        mx = fmaxf(mx, __shfl_xor_sync(0xffffffffu, mx, 1));
        mx = fmaxf(mx, __shfl_xor_sync(0xffffffffu, mx, 2));
        float m_new = fmaxf(m_run, mx);
        if (lane < 16 && jj == 0) mx_s[warp * 4 + rr] = m_new;
        bar_consumers();
#pragma unroll
        for (int w = 0; w < NCW; w++) m_new = fmaxf(m_new, mx_s[w * 4 + (rr & 3)]);
        if (__any_sync(0xffffffffu, m_new > m_run)) rescale(m_new);
        uint32_t pb[4];
        probs(sc, pb);
        l_run += __shfl_xor_sync(0xffffffffu, l_run, 1);
        l_run += __shfl_xor_sync(0xffffffffu, l_run, 2);
        if (lane < 16 && jj == 0) l_s[warp * 4 + rr] = l_run;
        uint4* pbuf = reinterpret_cast<uint4*>(sp + OFF_X);
        pbuf[tid] = make_uint4(pb[0], pb[1], pb[2], pb[3]);
        {
            float* dst = comb + warp * COMB_W + jj * 8 + rr;
#pragma unroll
            for (int m = 0; m < 4; m++)
#pragma unroll
                for (int e = 0; e < 4; e++) dst[(2 * m + (e >> 1)) * 80 + (e & 1) * 48] = o[m][e];
        }
        bar_consumers();
        if (tid < 16 && jj == 0) {
            float l = 0.f;
#pragma unroll
            for (int w = 0; w < NCW; w++) l += l_s[w * 4 + rr];
            st_rlx2(g_ml + (c * 4 + rr) * 2, tagw(m_run, tag), tagw(l, tag));
        }
        float2 prev;
        {
            const float* src = comb + warp * 80 + (rr & 1) * 48 + (rr >> 1) * 8 + jj * 2;
            prev = *reinterpret_cast<const float2*>(src);
#pragma unroll
            for (int w = 1; w < NCW; w++) {
                const float2 v = *reinterpret_cast<const float2*>(src + w * COMB_W);
                prev.x += v.x; prev.y += v.y;
            }
        }
        uint4 pf[NVP];
#pragma unroll
        for (int j = 0; j < NVP; j++) pf[j] = pbuf[j * 32 + lane];
        float acc[4][4];
#pragma unroll
        for (int u = 0; u < 4; u++)
#pragma unroll
            for (int e = 0; e < 4; e++) acc[u][e] = 0.f;
        acc[0][0] = prev.x; acc[0][1] = prev.y;
        const uint32_t vb = sb + OFF_RING + st * STAGE + lane * 128 + ((warp ^ r8) << 4);
#pragma unroll
        for (int j = 0; j < NVP; j++) {
            mbar_wait(bar_vp + j * 8, 0);
            uint32_t b0, b1, b2, b3;
            ldsm4t(vb + j * (STAGE / NVP), b0, b1, b2, b3);
            mma16816(acc[(j & 1) * 2], pf[j].x, 0u, pf[j].y, 0u, b0, b1);
            mma16816(acc[(j & 1) * 2 + 1], pf[j].z, 0u, pf[j].w, 0u, b2, b3);
        }
        TS(10);
        advance();
        st_rlx2(g_pa + (c * 4 + (rr & 3)) * kDH + (rr >> 2) * 64 + warp * 8 + jj * 2,
                tagw((acc[0][0] + acc[1][0]) + (acc[2][0] + acc[3][0]), tag),
                tagw((acc[0][1] + acc[1][1]) + (acc[2][1] + acc[3][1]), tag));
    }
    TS(11);

    uint32_t wf[8][4];
    auto load_wo = [&]() {
        const uint32_t wb = sb + OFF_RING + st * STAGE + (warp >> 2) * 16384 + ((mi >> 1) * 8 + r8) * 128 +
                            ((((warp & 3) * 2 + (mi & 1)) ^ r8) << 4);
#pragma unroll
        for (int ks = 0; ks < 8; ks++) ldsm4t(wb + ks * 2048, wf[ks][0], wf[ks][1], wf[ks][2], wf[ks][3]);
    };
    {
        const int hh = (c >> 2) & 3;
        const uint32_t* pm = g_ml + (((c & ~15) | ((warp >> 1) << 2)) * 4 + hh) * 2;
        const uint32_t* po = g_pa + (((c & ~15) | ((warp >> 1) << 2)) * 4 + hh) * kDH + (warp & 1) * 64 + lane * 2;
        uint2 v[4];
        auto load_pa = [&](uint2 (&d)[4]) {
#pragma unroll
            for (int s = 0; s < 4; s++) d[s] = ld_rlx2(po + s * (4 * kDH));
        };
        auto pa_ok = [&](const uint2 (&d)[4]) {
            return ((((d[0].x ^ tag) | (d[0].y ^ tag) | (d[1].x ^ tag) | (d[1].y ^ tag) | (d[2].x ^ tag) | (d[2].y ^ tag) |
                      (d[3].x ^ tag) | (d[3].y ^ tag)) & 1u) == 0);
        };
        spin(DLY_M);
        uint2 mlv[4];
#pragma unroll
        for (int s = 0; s < 4; s++) mlv[s] = ld_rlx2(pm + s * 8);
        int it = 0;
        while (!pa_ok(mlv)) {
            if (++it > (1 << 21)) __trap();
#pragma unroll
            for (int s = 0; s < 4; s++) mlv[s] = ld_rlx2(pm + s * 8);
        }
        TS(19);
        float w4[4];
        {
            const float ms[4] = {__uint_as_float(mlv[0].x), __uint_as_float(mlv[1].x), __uint_as_float(mlv[2].x), __uint_as_float(mlv[3].x)};
            const float ls[4] = {__uint_as_float(mlv[0].y), __uint_as_float(mlv[1].y), __uint_as_float(mlv[2].y), __uint_as_float(mlv[3].y)};
            const float M = fmaxf(fmaxf(ms[0], ms[1]), fmaxf(ms[2], ms[3]));
            float L = 0.f;
#pragma unroll
            for (int s = 0; s < 4; s++) {
                w4[s] = ex2((ms[s] - M) * kScaleLog2);
                L = fmaf(w4[s], ls[s], L);
            }
            const float inv = 1.f / L;
#pragma unroll
            for (int s = 0; s < 4; s++) w4[s] *= inv;
        }
        mbar_wait(bar_full + st * 8, ph);
        TS(20);
        load_pa(v);
        load_wo();
        while (!__all_sync(0xffffffffu, pa_ok(v))) {
            if (++it > (1 << 21)) __trap();
            load_pa(v);
        }
        TS(12);
        float z0 = 0.f, z1 = 0.f;
#pragma unroll
        for (int s = 0; s < 4; s++) {
            z0 = fmaf(w4[s], __uint_as_float(v[s].x), z0);
            z1 = fmaf(w4[s], __uint_as_float(v[s].y), z1);
        }
        *reinterpret_cast<uint32_t*>(sp + OFF_Q + ((warp >> 1) * QP + (warp & 1) * 64 + lane * 2) * 2) = pack_bf16(z0, z1);
    }
    bar_consumers();
    {
        const uint32_t oaddr = sb + OFF_Q + ((r8 & 3) * QP + mi * 8) * 2;
        float acc[4][4];
#pragma unroll
        for (int u = 0; u < 4; u++)
#pragma unroll
            for (int e = 0; e < 4; e++) acc[u][e] = 0.f;
#pragma unroll
        for (int kp = 0; kp < 4; kp++) {
            uint32_t b0, b1, b2, b3;
            ldsm4(oaddr + kp * 64, b0, b1, b2, b3);
            mma16816(acc[(kp & 1) * 2], wf[kp * 2][0], wf[kp * 2][1], wf[kp * 2][2], wf[kp * 2][3], b0, b1);
            mma16816(acc[(kp & 1) * 2 + 1], wf[kp * 2 + 1][0], wf[kp * 2 + 1][1], wf[kp * 2 + 1][2], wf[kp * 2 + 1][3], b2, b3);
        }
        if (jj < 2) {
            uint32_t* dst = g_pb + ((c >> 2) * kB + jj * 2) * kD + (c & 3) * 128 + warp * 16 + rr;
            st_rlx(dst, tagw((acc[0][0] + acc[1][0]) + (acc[2][0] + acc[3][0]), tag));
            st_rlx(dst + kD, tagw((acc[0][1] + acc[1][1]) + (acc[2][1] + acc[3][1]), tag));
            st_rlx(dst + 8, tagw((acc[0][2] + acc[1][2]) + (acc[2][2] + acc[3][2]), tag));
            st_rlx(dst + kD + 8, tagw((acc[0][3] + acc[1][3]) + (acc[2][3] + acc[3][3]), tag));
        }
    }
    TS(13);
    if (warp < 4) {
        const uint32_t* pbp = g_pb + (lane * kB + bf) * kD + col_f;
        spin(DLY_B);
        const uint4 v = poll4(pbp, tag);
        __syncwarp();
        TS(14);
        const float a[4] = {__uint_as_float(v.x), __uint_as_float(v.y), __uint_as_float(v.z), __uint_as_float(v.w)};
        const bool b0 = lane & 1, b1 = lane & 2;
        const float s0 = b0 ? a[0] : a[1], k0 = b0 ? a[1] : a[0];
        const float s1 = b0 ? a[2] : a[3], k1 = b0 ? a[3] : a[2];
        const float r0 = k0 + __shfl_xor_sync(0xffffffffu, s0, 1);
        const float r1 = k1 + __shfl_xor_sync(0xffffffffu, s1, 1);
        float r = (b1 ? r1 : r0) + __shfl_xor_sync(0xffffffffu, b1 ? r0 : r1, 2);
        r += __shfl_xor_sync(0xffffffffu, r, 4);
        r += __shfl_xor_sync(0xffffffffu, r, 8);
        r += __shfl_xor_sync(0xffffffffu, r, 16);
        if (lane < 4) {
            const float g = misc_f[0];
            const float f = b1 ? (b0 ? fsum[3] : fsum[2]) : (b0 ? fsum[1] : fsum[0]);
            prm.out[bf * kD + col_f + lane] = __float2bfloat16_rn(g * r + (1.f - g) * f);
            if (c == 0 && warp == 0 && lane == 0) {
                asm volatile("st.relaxed.gpu.global.u32 [%0], %1;" ::"l"(&g_epoch), "r"(epoch + 1u) : "memory");
            }
        }
        TS(15);
    }
}

typedef CUresult (*EncodeFn)(CUtensorMap*, CUtensorMapDataType, cuuint32_t, void*, const cuuint64_t*, const cuuint64_t*,
                             const cuuint32_t*, const cuuint32_t*, CUtensorMapInterleave, CUtensorMapSwizzle,
                             CUtensorMapL2promotion, CUtensorMapFloatOOBfill);

void encode2d(EncodeFn enc, CUtensorMap* m, const void* base, uint64_t cols, uint64_t rows, uint64_t pitch_bytes,
              uint32_t box_cols, uint32_t box_rows, CUtensorMapSwizzle swz) {
    cuuint64_t gd[2] = {cols, rows};
    cuuint64_t gs[1] = {pitch_bytes};
    cuuint32_t bd[2] = {box_cols, box_rows};
    cuuint32_t es[2] = {1, 1};
    enc(m, CU_TENSOR_MAP_DATA_TYPE_BFLOAT16, 2, const_cast<void*>(base), gd, gs, bd, es, CU_TENSOR_MAP_INTERLEAVE_NONE,
        swz, CU_TENSOR_MAP_L2_PROMOTION_L2_128B, CU_TENSOR_MAP_FLOAT_OOB_FILL_NONE);
}

}

extern "C" void kernel_launch(void* const* d_in, const int* in_sizes, int n_in, void* d_out, int out_size) {
    (void)in_sizes; (void)n_in; (void)out_size;
    static EncodeFn enc = nullptr;
    if (!enc) {
        void* fn = nullptr;
        cudaDriverEntryPointQueryResult qr;
        cudaGetDriverEntryPoint("cuTensorMapEncodeTiled", &fn, cudaEnableDefault, &qr);
        enc = reinterpret_cast<EncodeFn>(fn);
        cudaFuncSetAttribute(fused_decode_kernel, cudaFuncAttributeMaxDynamicSharedMemorySize, SMEM_BYTES);
    }
    CUtensorMap tk, tv, tvp, twq, two, twg, twu, twd;
    encode2d(enc, &tk, d_in[1], 64, (uint64_t)kB * kHKV * kSK * 2, 128, 64, 256, CU_TENSOR_MAP_SWIZZLE_128B);
    encode2d(enc, &tv, d_in[2], 64, (uint64_t)kB * kHKV * kSK * 2, 128, 64, 256, CU_TENSOR_MAP_SWIZZLE_128B);
    encode2d(enc, &tvp, d_in[2], 64, (uint64_t)kB * kHKV * kSK * 2, 128, 64, 256 / NVP, CU_TENSOR_MAP_SWIZZLE_128B);
    encode2d(enc, &twq, d_in[3], kHQ * kDH, kD, kHQ * kDH * 2, 32, 256, CU_TENSOR_MAP_SWIZZLE_64B);
    encode2d(enc, &two, d_in[4], kD, kHQ * kDH, kD * 2, 64, 128, CU_TENSOR_MAP_SWIZZLE_128B);
    encode2d(enc, &twg, d_in[6], kF, kD, kF * 2, 64, 256, CU_TENSOR_MAP_SWIZZLE_128B);
    encode2d(enc, &twu, d_in[7], kF, kD, kF * 2, 64, 256, CU_TENSOR_MAP_SWIZZLE_128B);
    encode2d(enc, &twd, d_in[8], kD, kF, kD * 2, 64, 64, CU_TENSOR_MAP_SWIZZLE_128B);
    Params prm;
    prm.x = reinterpret_cast<const __nv_bfloat16*>(d_in[0]);
    prm.gate_w = reinterpret_cast<const __nv_bfloat16*>(d_in[9]);
    prm.out = reinterpret_cast<__nv_bfloat16*>(d_out);
    fused_decode_kernel<<<NCTA, NTHREADS, SMEM_BYTES>>>(tk, tv, tvp, twq, two, twg, twu, twd, prm);
}
```

```cpp
#include <cuda_runtime.h>
#include <cuda_bf16.h>
#include <cuda.h>
#include <stdint.h>

#define EVICT_FIRST 1
#define WIN 2
#define INIT_WRITES 1
#define PACE 1
#define PACE_K 8
#define PACE_L0 (-112)
#define PACE_MAX 2000
#define WO_AT 7
#define DLY_D 1400
#define DLY_M 650
#define DLY_B 250

namespace {

constexpr int kB = 4, kD = 512, kHQ = 32, kHKV = 8, kDH = 128, kSK = 16384, kF = 1792;
constexpr int NATT = 128;
constexpr int NFFN = 4;
constexpr int NCTA = NATT + NFFN;
constexpr int NSTAGE = 6;
constexpr int STAGE = 32768;
constexpr int NCW = 8;
constexpr int NTHREADS = (NCW + 1) * 32;
constexpr int KEYS_PER_CTA = kSK / 4;
constexpr int NT = KEYS_PER_CTA / 128;
constexpr int ATT_STAGES = 2 + 2 * NT;
constexpr int FCOLS = kF / NFFN;
constexpr int FBLK = FCOLS / 64;
constexpr int FFN_STAGES = 4 * FBLK;
constexpr int DROWS = kF / kHQ;

constexpr int XP = 520;
constexpr int QP = 136;
constexpr int HP = 72;
constexpr int COMB_W = 640;
constexpr int OFF_RING = 0;
constexpr int OFF_COMB = NSTAGE * STAGE;
constexpr int OFF_X = OFF_COMB + NCW * COMB_W * 4;
constexpr int OFF_Q = OFF_X + kB * XP * 2;
constexpr int OFF_H = OFF_Q + kB * QP * 2;
constexpr int OFF_MX = OFF_H + kB * HP * 2;
constexpr int OFF_L = OFF_MX + NCW * 4 * 4;
constexpr int OFF_MISC = OFF_L + NCW * 4 * 4;
constexpr int OFF_BAR = OFF_MISC + 32;
constexpr int NVP = 8;
constexpr int SMEM_USED = OFF_BAR + (2 * NSTAGE + NVP) * 8;
constexpr int SMEM_BYTES = SMEM_USED + 1024;
static_assert(SMEM_BYTES <= 232448, "smem");
static_assert(OFF_X % 16 == 0 && OFF_Q % 16 == 0 && OFF_H % 16 == 0 && OFF_BAR % 8 == 0, "align");

constexpr float kScaleLog2 = 0.08838834764831845f * 1.4426950408889634f;

__device__ uint32_t g_epoch;
__device__ __align__(128) uint32_t g_prog[2 * 32];
__device__ __align__(128) uint32_t g_q[kB * kHQ * kDH];
__device__ __align__(128) uint32_t g_pa[NATT * 4 * kDH];
__device__ __align__(128) uint32_t g_ml[NATT * 4 * 2];
__device__ __align__(128) uint32_t g_h[kB * kF];
__device__ __align__(128) uint32_t g_pb[kHQ * kB * kD];

#define TS(i)
#define TSP(i)

__device__ __forceinline__ uint32_t smem_u32(const void* p) { return (uint32_t)__cvta_generic_to_shared(p); }
__device__ __forceinline__ void mbar_init(uint32_t bar, uint32_t cnt) {
    asm volatile("mbarrier.init.shared::cta.b64 [%0], %1;" ::"r"(bar), "r"(cnt));
}
__device__ __forceinline__ void mbar_expect_tx(uint32_t bar, uint32_t bytes) {
    asm volatile("mbarrier.arrive.expect_tx.shared::cta.b64 _, [%0], %1;" ::"r"(bar), "r"(bytes) : "memory");
}
__device__ __forceinline__ void mbar_arrive(uint32_t bar) {
    asm volatile("mbarrier.arrive.shared::cta.b64 _, [%0];" ::"r"(bar) : "memory");
}
__device__ __forceinline__ bool mbar_try_wait(uint32_t bar, uint32_t parity) {
    uint32_t ok;
    asm volatile("{\n.reg .pred p;\nmbarrier.try_wait.parity.shared::cta.b64 p, [%1], %2;\nselp.u32 %0, 1, 0, p;\n}"
                 : "=r"(ok) : "r"(bar), "r"(parity) : "memory");
    return ok;
}
__device__ __forceinline__ void mbar_wait(uint32_t bar, uint32_t parity) {
    if (mbar_try_wait(bar, parity)) return;
    const long long t0 = clock64();
    while (!mbar_try_wait(bar, parity)) {
        if (clock64() - t0 > 4000000000LL) __trap();
    }
}
__device__ __forceinline__ void tma2d(uint32_t dst, const CUtensorMap* m, int c0, int c1, uint32_t bar) {
    asm volatile("cp.async.bulk.tensor.2d.shared::cluster.global.mbarrier::complete_tx::bytes [%0], [%1, {%3, %4}], [%2];"
                 ::"r"(dst), "l"(m), "r"(bar), "r"(c0), "r"(c1) : "memory");
}
__device__ __forceinline__ void tma2d_hint(uint32_t dst, const CUtensorMap* m, int c0, int c1, uint32_t bar, uint64_t pol) {
    asm volatile("cp.async.bulk.tensor.2d.shared::cluster.global.mbarrier::complete_tx::bytes.L2::cache_hint"
                 " [%0], [%1, {%3, %4}], [%2], %5;"
                 ::"r"(dst), "l"(m), "r"(bar), "r"(c0), "r"(c1), "l"(pol) : "memory");
}
__device__ __forceinline__ void prefetch_tmap(const CUtensorMap* m) {
    asm volatile("prefetch.tensormap [%0];" ::"l"(m) : "memory");
}
__device__ __forceinline__ void ldsm4(uint32_t addr, uint32_t& r0, uint32_t& r1, uint32_t& r2, uint32_t& r3) {
    asm volatile("ldmatrix.sync.aligned.m8n8.x4.shared.b16 {%0,%1,%2,%3}, [%4];"
                 : "=r"(r0), "=r"(r1), "=r"(r2), "=r"(r3) : "r"(addr) : "memory");
}
__device__ __forceinline__ void ldsm4t(uint32_t addr, uint32_t& r0, uint32_t& r1, uint32_t& r2, uint32_t& r3) {
    asm volatile("ldmatrix.sync.aligned.m8n8.x4.trans.shared.b16 {%0,%1,%2,%3}, [%4];"
                 : "=r"(r0), "=r"(r1), "=r"(r2), "=r"(r3) : "r"(addr) : "memory");
}
__device__ __forceinline__ void mma16816(float (&c)[4], uint32_t a0, uint32_t a1, uint32_t a2, uint32_t a3,
                                         uint32_t b0, uint32_t b1) {
    asm volatile("mma.sync.aligned.m16n8k16.row.col.f32.bf16.bf16.f32 {%0,%1,%2,%3}, {%4,%5,%6,%7}, {%8,%9}, {%0,%1,%2,%3};"
                 : "+f"(c[0]), "+f"(c[1]), "+f"(c[2]), "+f"(c[3])
                 : "r"(a0), "r"(a1), "r"(a2), "r"(a3), "r"(b0), "r"(b1));
}
__device__ __forceinline__ void mma1688(float (&c)[4], uint32_t a0, uint32_t a1, uint32_t b0) {
    asm volatile("mma.sync.aligned.m16n8k8.row.col.f32.bf16.bf16.f32 {%0,%1,%2,%3}, {%4,%5}, {%6}, {%0,%1,%2,%3};"
                 : "+f"(c[0]), "+f"(c[1]), "+f"(c[2]), "+f"(c[3]) : "r"(a0), "r"(a1), "r"(b0));
}
__device__ __forceinline__ float ex2(float x) {
    float y;
    asm("ex2.approx.ftz.f32 %0, %1;" : "=f"(y) : "f"(x));
    return y;
}
__device__ __forceinline__ uint32_t pack_bf16(float lo, float hi) {
    uint32_t r;
    asm("cvt.rn.bf16x2.f32 %0, %1, %2;" : "=r"(r) : "f"(hi), "f"(lo));
    return r;
}
__device__ __forceinline__ float bf16_round(float v) { return __bfloat162float(__float2bfloat16_rn(v)); }
__device__ __forceinline__ void spin(int cycles) {
    const uint32_t t0 = clock();
    while ((int)(clock() - t0) < cycles) {}
}
__device__ __forceinline__ void bar_consumers() { asm volatile("bar.sync 1, 256;" ::: "memory"); }

__device__ __forceinline__ uint32_t tagw(float v, uint32_t tag) { return (__float_as_uint(v) & ~1u) | tag; }
__device__ __forceinline__ void st_rlx(uint32_t* p, uint32_t v) {
    asm volatile("st.relaxed.gpu.global.u32 [%0], %1;" ::"l"(p), "r"(v) : "memory");
}
__device__ __forceinline__ void st_rlx2(uint32_t* p, uint32_t a, uint32_t b) {
    asm volatile("st.relaxed.gpu.global.v2.u32 [%0], {%1,%2};" ::"l"(p), "r"(a), "r"(b) : "memory");
}
__device__ __forceinline__ uint4 ld_rlx4(const uint32_t* p) {
    uint4 v;
    asm volatile("ld.relaxed.gpu.global.v4.u32 {%0,%1,%2,%3}, [%4];"
                 : "=r"(v.x), "=r"(v.y), "=r"(v.z), "=r"(v.w) : "l"(p) : "memory");
    return v;
}
__device__ __forceinline__ uint2 ld_rlx2(const uint32_t* p) {
    uint2 v;
    asm volatile("ld.relaxed.gpu.global.v2.u32 {%0,%1}, [%2];" : "=r"(v.x), "=r"(v.y) : "l"(p) : "memory");
    return v;
}
__device__ __forceinline__ bool tag_ok(uint4 v, uint32_t tag) {
    return (((v.x ^ tag) | (v.y ^ tag) | (v.z ^ tag) | (v.w ^ tag)) & 1u) == 0;
}
__device__ __forceinline__ uint4 poll4(const uint32_t* p, uint32_t tag) {
    uint4 v = ld_rlx4(p);
    int it = 0;
    while (!tag_ok(v, tag)) {
        if (++it > (1 << 21)) __trap();
        v = ld_rlx4(p);
    }
    return v;
}

__device__ __forceinline__ int tile_line(int c, int t) {
    return (((c >> 2) & 3) * kHKV + (c >> 4)) * (kSK * 2) + (t * 4 + (c & 3)) * 256;
}

struct Params {
    const __nv_bfloat16* x;
    const __nv_bfloat16* gate_w;
    __nv_bfloat16* out;
};

__global__ void __launch_bounds__(NTHREADS, 1)
fused_decode_kernel(const __grid_constant__ CUtensorMap tm_k, const __grid_constant__ CUtensorMap tm_v,
                    const __grid_constant__ CUtensorMap tm_vp,
                    const __grid_constant__ CUtensorMap tm_wq, const __grid_constant__ CUtensorMap tm_wo,
                    const __grid_constant__ CUtensorMap tm_wg, const __grid_constant__ CUtensorMap tm_wu,
                    const __grid_constant__ CUtensorMap tm_wd, const Params prm) {
    extern __shared__ uint8_t smem_raw[];
    const uint32_t sraw = smem_u32(smem_raw);
    uint32_t sb = (sraw + 1023u) & ~1023u;
    uint64_t p_wq = reinterpret_cast<uint64_t>(&tm_wq), p_k = reinterpret_cast<uint64_t>(&tm_k);
    asm volatile("" : "+r"(sb), "+l"(p_wq), "+l"(p_k));
    uint8_t* sp = smem_raw + (((sraw + 1023u) & ~1023u) - sraw);
    const int tid = threadIdx.x, warp = tid >> 5, lane = tid & 31;
    const int c = blockIdx.x;
    const bool is_ffn = c >= NATT;
    const uint32_t bar_full = sb + OFF_BAR, bar_empty = bar_full + NSTAGE * 8, bar_vp = bar_empty + NSTAGE * 8;

    TS(0);
    if (warp == NCW) {
        uint64_t pol0;
        asm volatile("createpolicy.fractional.L2::evict_first.b64 %0, 1.0;" : "=l"(pol0));
        if (lane == 0) {
            for (int s = 0; s < WIN; s++) mbar_init(bar_full + s * 8, 1);
            asm volatile("fence.proxy.async.shared::cta;" ::: "memory");
            if (!is_ffn) {
                static_assert(WIN == 2, "the prologue issues stage 0 (wq) and stage 1 (first K tile)");
                const int l0 = tile_line(c, 0);
                mbar_expect_tx(bar_full, STAGE);
                tma2d(sb + OFF_RING, reinterpret_cast<const CUtensorMap*>(p_wq), 32 * c, 0, bar_full);
                tma2d(sb + OFF_RING + STAGE / 2, reinterpret_cast<const CUtensorMap*>(p_wq), 32 * c, 256, bar_full);
                mbar_expect_tx(bar_full + 8, STAGE);
                tma2d_hint(sb + OFF_RING + STAGE, reinterpret_cast<const CUtensorMap*>(p_k), 0, l0, bar_full + 8, pol0);
            }
        }
        const int nst = is_ffn ? FFN_STAGES : ATT_STAGES;
        const int f0 = (c - NATT) * FCOLS;
        uint64_t pol;
        asm volatile("createpolicy.fractional.L2::evict_first.b64 %0, 1.0;" : "=l"(pol));
        auto issue = [&](int i, int s) {
            const uint32_t bar = bar_full + s * 8, dst = sb + OFF_RING + s * STAGE;
            if (!is_ffn && i == 2 * NT) {
#pragma unroll 1
                for (int j = 0; j < NVP; j++) {
                    mbar_expect_tx(bar_vp + j * 8, STAGE / NVP);
                    tma2d_hint(dst + j * (STAGE / NVP), &tm_vp, 0, tile_line(c, NT - 1) + j * (256 / NVP), bar_vp + j * 8, pol);
                }
                return;
            }
            mbar_expect_tx(bar, STAGE);
            if (!is_ffn) {
                if (i == 0) {
                    tma2d(dst, &tm_wq, 32 * c, 0, bar);
                    tma2d(dst + STAGE / 2, &tm_wq, 32 * c, 256, bar);
                } else if (i <= 2 * NT) {
                    const int t = (i - 1) >> 1;
                    tma2d_hint(dst, ((i - 1) & 1) ? &tm_v : &tm_k, 0, tile_line(c, t), bar, pol);
                } else {
                    tma2d(dst, &tm_wo, 128 * (c & 3), 128 * (c >> 2), bar);
                    tma2d(dst + STAGE / 2, &tm_wo, 128 * (c & 3) + 64, 128 * (c >> 2), bar);
                }
            } else {
                tma2d(dst, (i & 2) ? &tm_wu : &tm_wg, f0 + 64 * (i >> 2), 256 * (i & 1), bar);
            }
        };
        if (lane == 0) {
            TSP(16);
            if (is_ffn) for (int s = 0; s < WIN; s++) issue(s, s);
            TSP(17);
            for (int s = 0; s < NSTAGE; s++) {
                if (s >= WIN) mbar_init(bar_full + s * 8, 1);
                mbar_init(bar_empty + s * 8, NCW);
            }
            for (int s = 0; s < NVP; s++) mbar_init(bar_vp + s * 8, 1);
            asm volatile("fence.mbarrier_init.release.cluster;" ::: "memory");
            asm volatile("fence.proxy.async.shared::cta;" ::: "memory");
        }
        __syncthreads();
        if (lane == 0) {
            int s = WIN % NSTAGE, sw = 0;
            uint32_t ph = WIN == NSTAGE ? 0 : 1, phw = 0;
            const uint32_t ep = *reinterpret_cast<volatile uint32_t*>(sp + OFF_MISC + 4);
            uint32_t* prog = g_prog + (ep & 1u) * 32;
            if (c == 0) st_rlx(g_prog + ((ep + 1u) & 1u) * 32, 0u);
            uint32_t r_old = 0;
            int dly = 0;
            for (int i = WIN; i < nst; i++) {
                mbar_wait(bar_full + sw * 8, phw);
                const uint32_t t0 = clock();
                if (!is_ffn && (i & 1)) {
                    if (i >= 5) dly = min(max((64 * (i - 3) - (int)r_old - 1 - (PACE_L0)) * PACE_K, 0), PACE_MAX);
                    asm volatile("atom.relaxed.gpu.global.inc.u32 %0, [%1], 0x7fffffff;" : "=r"(r_old) : "l"(prog) : "memory");
                }
                if (i >= NSTAGE) mbar_wait(bar_empty + s * 8, ph);
                if (WO_AT >= 0 && !is_ffn && i == ATT_STAGES - 1) {
                    mbar_wait(bar_vp + (WO_AT < 0 ? 0 : WO_AT) * 8, 0);
                }
                while ((int)(clock() - t0) < dly) {}
                issue(i, s);
                if (++s == NSTAGE) { s = 0; ph ^= 1; }
                if (++sw == NSTAGE) { sw = 0; phw ^= 1; }
            }
            if (!is_ffn) {
                static_assert(ATT_STAGES % NSTAGE == 0 && ((ATT_STAGES / NSTAGE) & 1), "slot / parity of the W_down stage");
                spin(DLY_D);
                mbar_wait(bar_empty, 0);
                mbar_expect_tx(bar_full, DROWS * 256);
                tma2d(sb + OFF_RING, &tm_wd, 128 * (c & 3), DROWS * (c >> 2), bar_full);
                tma2d(sb + OFF_RING + 8192, &tm_wd, 128 * (c & 3) + 64, DROWS * (c >> 2), bar_full);
            }
            TSP(18);
        }
        return;
    }

    {
        const uint4 xv = __ldg(reinterpret_cast<const uint4*>(prm.x) + tid);
        *reinterpret_cast<uint4*>(sp + OFF_X + ((tid >> 6) * XP + (tid & 63) * 8) * 2) = xv;
    }
    float* misc_f = reinterpret_cast<float*>(sp + OFF_MISC);
    uint32_t* misc_u = reinterpret_cast<uint32_t*>(sp + OFF_MISC);
    if (tid == 0) {
        uint32_t e;
        asm volatile("ld.relaxed.gpu.global.u32 %0, [%1];" : "=r"(e) : "l"(&g_epoch) : "memory");
        misc_u[1] = e;
    }
    if (warp >= NCW - kB && !is_ffn) {
        const int bf = warp - (NCW - kB);
        const uint4* xp = reinterpret_cast<const uint4*>(prm.x + bf * kD) + lane * 2;
        const uint4* gp = reinterpret_cast<const uint4*>(prm.gate_w) + lane * 2;
        float acc = 0.f;
#pragma unroll
        for (int u = 0; u < 2; u++) {
            const uint4 a = __ldg(xp + u), g = __ldg(gp + u);
            const uint32_t aw[4] = {a.x, a.y, a.z, a.w}, gw[4] = {g.x, g.y, g.z, g.w};
#pragma unroll
            for (int e = 0; e < 4; e++) {
                acc = fmaf(__uint_as_float(aw[e] << 16), __uint_as_float(gw[e] << 16), acc);
                acc = fmaf(__uint_as_float(aw[e] & 0xffff0000u), __uint_as_float(gw[e] & 0xffff0000u), acc);
            }
        }
#pragma unroll
        for (int o = 16; o > 0; o >>= 1) acc += __shfl_xor_sync(0xffffffffu, acc, o);
        if (lane == 0) misc_f[4 + bf] = 1.f / (1.f + __expf(-acc));
    }
    __syncthreads();
    TS(1);
    const uint32_t epoch = misc_u[1];
    const uint32_t tag = (epoch + 1u) & 1u;

    const int r8 = lane & 7, mi = lane >> 3;
    const int rr = lane >> 2, jj = lane & 3;
    int st = 0;
    uint32_t ph = 0;
    auto advance = [&]() { if (++st == NSTAGE) { st = 0; ph ^= 1; } };
    auto release = [&]() {
        __syncwarp();
        if (lane == 0) mbar_arrive(bar_empty + st * 8);
        advance();
    };
    const uint32_t x_addr = sb + OFF_X + ((r8 & 3) * XP + mi * 8) * 2;

    if (is_ffn) {
        uint32_t* hdst = g_h + (rr & 3) * kF + (c - NATT) * FCOLS + warp * 8 + jj * 2;
        if (lane < 16) {
#pragma unroll
            for (int jb = 0; jb < FBLK; jb++) st_rlx2(hdst + jb * 64, tag ^ 1u, tag ^ 1u);
        }
        for (int jb = 0; jb < FBLK; jb++) {
            float gu[2][2][4];
#pragma unroll
            for (int m = 0; m < 2; m++) {
#pragma unroll
                for (int e = 0; e < 4; e++) gu[m][0][e] = gu[m][1][e] = 0.f;
#pragma unroll
                for (int kh = 0; kh < 2; kh++) {
                    mbar_wait(bar_full + st * 8, ph);
                    const uint32_t wb = sb + OFF_RING + st * STAGE + lane * 128 + ((warp ^ r8) << 4);
#pragma unroll
                    for (int kk = 0; kk < 8; kk++) {
                        uint32_t b0, b1, b2, b3, a0, a1, a2, a3;
                        ldsm4t(wb + kk * 4096, b0, b1, b2, b3);
                        ldsm4(x_addr + (kh * 256 + kk * 32) * 2, a0, a1, a2, a3);
                        mma16816(gu[m][0], a0, 0u, a1, 0u, b0, b1);
                        mma16816(gu[m][1], a2, 0u, a3, 0u, b2, b3);
                    }
                    release();
                }
            }
            const float g0 = bf16_round(gu[0][0][0] + gu[0][1][0]), g1 = bf16_round(gu[0][0][1] + gu[0][1][1]);
            const float u0 = bf16_round(gu[1][0][0] + gu[1][1][0]), u1 = bf16_round(gu[1][0][1] + gu[1][1][1]);
            const float h0 = (g0 > 0.f ? g0 : 0.f) * u0, h1 = (g1 > 0.f ? g1 : 0.f) * u1;
            if (lane < 16) st_rlx2(hdst + jb * 64, tagw(bf16_round(h0), tag), tagw(bf16_round(h1), tag));
        }
        TS(15);
        return;
    }

    float* comb = reinterpret_cast<float*>(sp + OFF_COMB);
    float* mx_s = reinterpret_cast<float*>(sp + OFF_MX);
    float* l_s = reinterpret_cast<float*>(sp + OFF_L);
    const int hkv = c >> 4, batch = (c >> 2) & 3;
    {
        const uint32_t nr = tag ^ 1u;
        if (tid < 128) st_rlx(g_q + (tid >> 5) * (kHQ * kDH) + 32 * c + (tid & 31), nr);
        st_rlx2(g_pa + (c * 4 + (rr & 3)) * kDH + (rr >> 2) * 64 + warp * 8 + jj * 2, nr, nr);
        if (tid < 16 && jj == 0) st_rlx2(g_ml + (c * 4 + rr) * 2, nr, nr);
        if (jj < 2) {
            uint32_t* d2 = g_pb + ((c >> 2) * kB + jj * 2) * kD + (c & 3) * 128 + warp * 16 + rr;
            st_rlx(d2, nr);
            st_rlx(d2 + kD, nr);
            st_rlx(d2 + 8, nr);
            st_rlx(d2 + kD + 8, nr);
        }
    }

    {
        float qc[4][4];
#pragma unroll
        for (int n = 0; n < 4; n++)
#pragma unroll
            for (int e = 0; e < 4; e++) qc[n][e] = 0.f;
        uint32_t a[8];
        ldsm4(x_addr + (warp * 64) * 2, a[0], a[1], a[2], a[3]);
        ldsm4(x_addr + (warp * 64 + 32) * 2, a[4], a[5], a[6], a[7]);
        mbar_wait(bar_full + st * 8, ph);
        TS(2);
#pragma unroll
        for (int ks = 0; ks < 4; ks++) {
            const int row = warp * 64 + ks * 16 + (lane & 15);
#pragma unroll
            for (int np = 0; np < 2; np++) {
                uint32_t b0, b1, b2, b3;
                const int chunk = np * 2 + (lane >> 4);
                ldsm4t(sb + OFF_RING + st * STAGE + row * 64 + ((chunk ^ ((row >> 1) & 3)) << 4), b0, b1, b2, b3);
                mma16816(qc[np * 2], a[ks * 2], 0u, a[ks * 2 + 1], 0u, b0, b1);
                mma16816(qc[np * 2 + 1], a[ks * 2], 0u, a[ks * 2 + 1], 0u, b2, b3);
            }
        }
        release();
        if (lane < 16) {
#pragma unroll
            for (int n = 0; n < 4; n++)
                *reinterpret_cast<float2*>(comb + warp * 128 + rr * 32 + n * 8 + jj * 2) = make_float2(qc[n][0], qc[n][1]);
        }
        bar_consumers();
        if (tid < 128) {
            float s = 0.f;
#pragma unroll
            for (int w = 0; w < NCW; w++) s += comb[w * 128 + tid];
            st_rlx(g_q + (tid >> 5) * (kHQ * kDH) + 32 * c + (tid & 31), tagw(s, tag));
            TS(3);
            const uint32_t* qsrc = g_q + batch * (kHQ * kDH) + hkv * 512 + tid * 4;
            uint4 v = ld_rlx4(qsrc);
            int it = 0;
            while (!tag_ok(v, tag)) {
                if (++it > (1 << 21)) __trap();
                __nanosleep(64);
                v = ld_rlx4(qsrc);
            }
            uint2 pk;
            pk.x = pack_bf16(__uint_as_float(v.x), __uint_as_float(v.y));
            pk.y = pack_bf16(__uint_as_float(v.z), __uint_as_float(v.w));
            *reinterpret_cast<uint2*>(sp + OFF_Q + ((tid >> 5) * QP + (tid & 31) * 4) * 2) = pk;
        }
        bar_consumers();
    }
    TS(4);
    uint32_t qa[8];
    {
        const uint32_t qaddr = sb + OFF_Q + ((r8 & 3) * QP + (r8 >> 2) * 64 + mi * 8) * 2;
        ldsm4(qaddr, qa[0], qa[1], qa[2], qa[3]);
        ldsm4(qaddr + 64, qa[4], qa[5], qa[6], qa[7]);
    }

    float o[4][4];
#pragma unroll
    for (int m = 0; m < 4; m++)
#pragma unroll
        for (int e = 0; e < 4; e++) o[m][e] = 0.f;
    float m_run = -INFINITY, l_run = 0.f;
    const uint32_t k_off = (warp * 32 + r8) * 128 + ((mi ^ r8) << 4);
    const uint32_t v_off = (warp * 32 + (mi >> 1) * 8 + r8) * 128 + (((mi & 1) ^ r8) << 4);
    const uint32_t pmask = lane < 16 ? 0x0000ffffu : 0xffff0000u;
    const int bf = c >> 5, col_f = (c & 31) * 16 + (warp & 3) * 4;

    auto scores = [&](float (&sc)[4]) {
        float s[4][4];
        const uint32_t kb = sb + OFF_RING + st * STAGE;
#pragma unroll
        for (int g = 0; g < 4; g++) {
#pragma unroll
            for (int e = 0; e < 4; e++) s[g][e] = 0.f;
            uint32_t b0, b1, b2, b3;
            ldsm4(kb + k_off + g * 1024, b0, b1, b2, b3);
            mma16816(s[g], qa[0], 0u, qa[1], 0u, b0, b1);
            mma16816(s[g], qa[2], 0u, qa[3], 0u, b2, b3);
            ldsm4(kb + (k_off ^ 64u) + g * 1024, b0, b1, b2, b3);
            mma16816(s[g], qa[4], 0u, qa[5], 0u, b0, b1);
            mma16816(s[g], qa[6], 0u, qa[7], 0u, b2, b3);
        }
        release();
#pragma unroll
        for (int g = 0; g < 4; g++) {
            const float v = lane < 16 ? s[g][0] : s[g][1];
            sc[g] = v + __shfl_xor_sync(0xffffffffu, v, 16);
        }
    };
    auto rescale = [&](float m_new) {
        const float alpha = ex2((m_run - m_new) * kScaleLog2);
        l_run *= alpha;
        const float a0 = __shfl_sync(0xffffffffu, alpha, ((2 * jj) & 3) * 4);
        const float a1 = __shfl_sync(0xffffffffu, alpha, ((2 * jj + 1) & 3) * 4);
#pragma unroll
        for (int m = 0; m < 4; m++) {
            o[m][0] *= a0; o[m][1] *= a1; o[m][2] *= a0; o[m][3] *= a1;
        }
        m_run = m_new;
    };
    auto probs = [&](const float (&sc)[4], uint32_t (&pb)[4]) {
        const float mc = m_run * kScaleLog2;
#pragma unroll
        for (int g = 0; g < 4; g++) {
            const float p = ex2(fmaf(sc[g], kScaleLog2, -mc));
            l_run += p;
            pb[g] = pack_bf16(p, p) & pmask;
        }
    };

    for (int t = 0; t < NT - 1; t++) {
        mbar_wait(bar_full + st * 8, ph);
        float sc[4];
        scores(sc);
        float mx = fmaxf(fmaxf(sc[0], sc[1]), fmaxf(sc[2], sc[3]));
        mx = fmaxf(mx, __shfl_xor_sync(0xffffffffu, mx, 1));
        mx = fmaxf(mx, __shfl_xor_sync(0xffffffffu, mx, 2));
        const float m_new = fmaxf(m_run, mx);
        if (__any_sync(0xffffffffu, m_new > m_run)) rescale(m_new);
        uint32_t pb[4];
        probs(sc, pb);
        if (t == NT - 4 && warp < kB && lane < DROWS / 4) {
            const uint4 v = poll4(g_h + warp * kF + (c >> 2) * DROWS + lane * 4, tag);
            uint2 pk;
            pk.x = __byte_perm(v.x, v.y, 0x7632);
            pk.y = __byte_perm(v.z, v.w, 0x7632);
            *reinterpret_cast<uint2*>(sp + OFF_H + (warp * HP + lane * 4) * 2) = pk;
        }
        __syncwarp();
        mbar_wait(bar_full + st * 8, ph);
        {
            const uint32_t vb = sb + OFF_RING + st * STAGE;
#pragma unroll
            for (int oc = 0; oc < 2; oc++) {
#pragma unroll
                for (int m = 0; m < 4; m++) {
                    uint32_t a0, a1, a2, a3;
                    ldsm4t(vb + ((v_off + oc * 2048) ^ (m * 32)), a0, a1, a2, a3);
                    mma16816(o[m], a0, a1, a2, a3, pb[oc * 2], pb[oc * 2 + 1]);
                }
            }
        }
        release();
    }

    {
        mbar_wait(bar_full + st * 8, ph);
        TS(9);
        float sc[4];
        scores(sc);
        float mx = fmaxf(fmaxf(sc[0], sc[1]), fmaxf(sc[2], sc[3]));
        mx = fmaxf(mx, __shfl_xor_sync(0xffffffffu, mx, 1));
        mx = fmaxf(mx, __shfl_xor_sync(0xffffffffu, mx, 2));
        float m_new = fmaxf(m_run, mx);
        if (lane < 16 && jj == 0) mx_s[warp * 4 + rr] = m_new;
        bar_consumers();
#pragma unroll
        for (int w = 0; w < NCW; w++) m_new = fmaxf(m_new, mx_s[w * 4 + (rr & 3)]);
        if (__any_sync(0xffffffffu, m_new > m_run)) rescale(m_new);
        uint32_t pb[4];
        probs(sc, pb);
        l_run += __shfl_xor_sync(0xffffffffu, l_run, 1);
        l_run += __shfl_xor_sync(0xffffffffu, l_run, 2);
        if (lane < 16 && jj == 0) l_s[warp * 4 + rr] = l_run;
        uint4* pbuf = reinterpret_cast<uint4*>(sp + OFF_X);
        pbuf[tid] = make_uint4(pb[0], pb[1], pb[2], pb[3]);
        {
            float* dst = comb + warp * COMB_W + jj * 8 + rr;
#pragma unroll
            for (int m = 0; m < 4; m++)
#pragma unroll
                for (int e = 0; e < 4; e++) dst[(2 * m + (e >> 1)) * 80 + (e & 1) * 48] = o[m][e];
        }
        bar_consumers();
        if (tid < 16 && jj == 0) {
            float l = 0.f;
#pragma unroll
            for (int w = 0; w < NCW; w++) l += l_s[w * 4 + rr];
            st_rlx2(g_ml + (c * 4 + rr) * 2, tagw(m_run, tag), tagw(l, tag));
        }
        float2 prev;
        {
            const float* src = comb + warp * 80 + (rr & 1) * 48 + (rr >> 1) * 8 + jj * 2;
            prev = *reinterpret_cast<const float2*>(src);
#pragma unroll
            for (int w = 1; w < NCW; w++) {
                const float2 v = *reinterpret_cast<const float2*>(src + w * COMB_W);
                prev.x += v.x; prev.y += v.y;
            }
        }
        uint4 pf[NVP];
#pragma unroll
        for (int j = 0; j < NVP; j++) pf[j] = pbuf[j * 32 + lane];
        float acc[4][4];
#pragma unroll
        for (int u = 0; u < 4; u++)
#pragma unroll
            for (int e = 0; e < 4; e++) acc[u][e] = 0.f;
        acc[0][0] = prev.x; acc[0][1] = prev.y;
        const uint32_t vb = sb + OFF_RING + st * STAGE + lane * 128 + ((warp ^ r8) << 4);
#pragma unroll
        for (int j = 0; j < NVP; j++) {
            mbar_wait(bar_vp + j * 8, 0);
            uint32_t b0, b1, b2, b3;
            ldsm4t(vb + j * (STAGE / NVP), b0, b1, b2, b3);
            mma16816(acc[(j & 1) * 2], pf[j].x, 0u, pf[j].y, 0u, b0, b1);
            mma16816(acc[(j & 1) * 2 + 1], pf[j].z, 0u, pf[j].w, 0u, b2, b3);
        }
        TS(10);
        advance();
        st_rlx2(g_pa + (c * 4 + (rr & 3)) * kDH + (rr >> 2) * 64 + warp * 8 + jj * 2,
                tagw((acc[0][0] + acc[1][0]) + (acc[2][0] + acc[3][0]), tag),
                tagw((acc[0][1] + acc[1][1]) + (acc[2][1] + acc[3][1]), tag));
    }
    TS(11);

    uint32_t wf[8][4];
    auto load_wo = [&]() {
        const uint32_t wb = sb + OFF_RING + st * STAGE + (warp >> 2) * 16384 + ((mi >> 1) * 8 + r8) * 128 +
                            ((((warp & 3) * 2 + (mi & 1)) ^ r8) << 4);
#pragma unroll
        for (int ks = 0; ks < 8; ks++) ldsm4t(wb + ks * 2048, wf[ks][0], wf[ks][1], wf[ks][2], wf[ks][3]);
    };
    {
        const int hh = (c >> 2) & 3;
        const uint32_t* pm = g_ml + (((c & ~15) | ((warp >> 1) << 2)) * 4 + hh) * 2;
        const uint32_t* po = g_pa + (((c & ~15) | ((warp >> 1) << 2)) * 4 + hh) * kDH + (warp & 1) * 64 + lane * 2;
        uint2 v[4];
        auto load_pa = [&](uint2 (&d)[4]) {
#pragma unroll
            for (int s = 0; s < 4; s++) d[s] = ld_rlx2(po + s * (4 * kDH));
        };
        auto pa_ok = [&](const uint2 (&d)[4]) {
            return ((((d[0].x ^ tag) | (d[0].y ^ tag) | (d[1].x ^ tag) | (d[1].y ^ tag) | (d[2].x ^ tag) | (d[2].y ^ tag) |
                      (d[3].x ^ tag) | (d[3].y ^ tag)) & 1u) == 0);
        };
        spin(DLY_M);
        uint2 mlv[4];
#pragma unroll
        for (int s = 0; s < 4; s++) mlv[s] = ld_rlx2(pm + s * 8);
        int it = 0;
        while (!pa_ok(mlv)) {
            if (++it > (1 << 21)) __trap();
#pragma unroll
            for (int s = 0; s < 4; s++) mlv[s] = ld_rlx2(pm + s * 8);
        }
        TS(19);
        float w4[4];
        {
            const float ms[4] = {__uint_as_float(mlv[0].x), __uint_as_float(mlv[1].x), __uint_as_float(mlv[2].x), __uint_as_float(mlv[3].x)};
            const float ls[4] = {__uint_as_float(mlv[0].y), __uint_as_float(mlv[1].y), __uint_as_float(mlv[2].y), __uint_as_float(mlv[3].y)};
            const float M = fmaxf(fmaxf(ms[0], ms[1]), fmaxf(ms[2], ms[3]));
            float L = 0.f;
#pragma unroll
            for (int s = 0; s < 4; s++) {
                w4[s] = ex2((ms[s] - M) * kScaleLog2);
                L = fmaf(w4[s], ls[s], L);
            }
            const float inv = 1.f / L;
#pragma unroll
            for (int s = 0; s < 4; s++) w4[s] *= inv;
        }
        mbar_wait(bar_full + st * 8, ph);
        TS(20);
        load_pa(v);
        load_wo();
        while (!__all_sync(0xffffffffu, pa_ok(v))) {
            if (++it > (1 << 21)) __trap();
            load_pa(v);
        }
        TS(12);
        float z0 = 0.f, z1 = 0.f;
#pragma unroll
        for (int s = 0; s < 4; s++) {
            z0 = fmaf(w4[s], __uint_as_float(v[s].x), z0);
            z1 = fmaf(w4[s], __uint_as_float(v[s].y), z1);
        }
        *reinterpret_cast<uint32_t*>(sp + OFF_Q + ((warp >> 1) * QP + (warp & 1) * 64 + lane * 2) * 2) = pack_bf16(z0, z1);
    }
    bar_consumers();
    {
        const uint32_t oaddr = sb + OFF_Q + ((r8 & 3) * QP + mi * 8) * 2;
        const uint32_t haddr = sb + OFF_H + ((r8 & 3) * HP + mi * 8) * 2;
        uint32_t hb[8];
        ldsm4(haddr, hb[0], hb[1], hb[2], hb[3]);
        ldsm4(haddr + 64, hb[4], hb[5], hb[6], hb[7]);
        const float g0 = misc_f[4 + (jj & 1) * 2], g1 = misc_f[5 + (jj & 1) * 2];
        float acc[4][4];
#pragma unroll
        for (int u = 0; u < 4; u++)
#pragma unroll
            for (int e = 0; e < 4; e++) acc[u][e] = 0.f;
#pragma unroll
        for (int kp = 0; kp < 4; kp++) {
            uint32_t b0, b1, b2, b3;
            ldsm4(oaddr + kp * 64, b0, b1, b2, b3);
            mma16816(acc[(kp & 1) * 2], wf[kp * 2][0], wf[kp * 2][1], wf[kp * 2][2], wf[kp * 2][3], b0, b1);
            mma16816(acc[(kp & 1) * 2 + 1], wf[kp * 2 + 1][0], wf[kp * 2 + 1][1], wf[kp * 2 + 1][2], wf[kp * 2 + 1][3], b2, b3);
        }
        float att[4];
#pragma unroll
        for (int e = 0; e < 4; e++) att[e] = ((acc[0][e] + acc[1][e]) + (acc[2][e] + acc[3][e])) * ((e & 1) ? g1 : g0);
        float fa[2][4];
#pragma unroll
        for (int e = 0; e < 4; e++) fa[0][e] = fa[1][e] = 0.f;
        mbar_wait(bar_full, 1);
        {
            const uint32_t db = sb + OFF_RING + (warp >> 2) * 8192 + ((mi >> 1) * 8 + r8) * 128 +
                                ((((warp & 3) * 2 + (mi & 1)) ^ r8) << 4);
            uint32_t d0[4], d1[4], d2[4], d3[4];
            ldsm4t(db, d0[0], d0[1], d0[2], d0[3]);
            ldsm4t(db + 2048, d1[0], d1[1], d1[2], d1[3]);
            ldsm4t(db + 4096, d2[0], d2[1], d2[2], d2[3]);
            ldsm4t(db + 6144, d3[0], d3[1], d3[2], d3[3]);
            mma16816(fa[0], d0[0], d0[1], d0[2], d0[3], hb[0], hb[1]);
            mma16816(fa[1], d1[0], d1[1], d1[2], d1[3], hb[2], hb[3]);
            mma16816(fa[0], d2[0], d2[1], d2[2], d2[3], hb[4], hb[5]);
            mma1688(fa[1], d3[0], d3[1], hb[6]);
        }
        if (jj < 2) {
            uint32_t* dst = g_pb + ((c >> 2) * kB + jj * 2) * kD + (c & 3) * 128 + warp * 16 + rr;
            st_rlx(dst, tagw(fmaf(fa[0][0] + fa[1][0], 1.f - g0, att[0]), tag));
            st_rlx(dst + kD, tagw(fmaf(fa[0][1] + fa[1][1], 1.f - g1, att[1]), tag));
            st_rlx(dst + 8, tagw(fmaf(fa[0][2] + fa[1][2], 1.f - g0, att[2]), tag));
            st_rlx(dst + kD + 8, tagw(fmaf(fa[0][3] + fa[1][3], 1.f - g1, att[3]), tag));
        }
    }
    TS(13);
    if (warp < 4) {
        const uint32_t* pbp = g_pb + (lane * kB + bf) * kD + col_f;
        spin(DLY_B);
        const uint4 v = poll4(pbp, tag);
        __syncwarp();
        TS(14);
        const float a[4] = {__uint_as_float(v.x), __uint_as_float(v.y), __uint_as_float(v.z), __uint_as_float(v.w)};
        const bool b0 = lane & 1, b1 = lane & 2;
        const float s0 = b0 ? a[0] : a[1], k0 = b0 ? a[1] : a[0];
        const float s1 = b0 ? a[2] : a[3], k1 = b0 ? a[3] : a[2];
        const float r0 = k0 + __shfl_xor_sync(0xffffffffu, s0, 1);
        const float r1 = k1 + __shfl_xor_sync(0xffffffffu, s1, 1);
        float r = (b1 ? r1 : r0) + __shfl_xor_sync(0xffffffffu, b1 ? r0 : r1, 2);
        r += __shfl_xor_sync(0xffffffffu, r, 4);
        r += __shfl_xor_sync(0xffffffffu, r, 8);
        r += __shfl_xor_sync(0xffffffffu, r, 16);
        if (lane < 4) {
            prm.out[bf * kD + col_f + lane] = __float2bfloat16_rn(r);
            if (c == 0 && warp == 0 && lane == 0) {
                asm volatile("st.relaxed.gpu.global.u32 [%0], %1;" ::"l"(&g_epoch), "r"(epoch + 1u) : "memory");
            }
        }
        TS(15);
    }
}

typedef CUresult (*EncodeFn)(CUtensorMap*, CUtensorMapDataType, cuuint32_t, void*, const cuuint64_t*, const cuuint64_t*,
                             const cuuint32_t*, const cuuint32_t*, CUtensorMapInterleave, CUtensorMapSwizzle,
                             CUtensorMapL2promotion, CUtensorMapFloatOOBfill);

void encode2d(EncodeFn enc, CUtensorMap* m, const void* base, uint64_t cols, uint64_t rows, uint64_t pitch_bytes,
              uint32_t box_cols, uint32_t box_rows, CUtensorMapSwizzle swz) {
    cuuint64_t gd[2] = {cols, rows};
    cuuint64_t gs[1] = {pitch_bytes};
    cuuint32_t bd[2] = {box_cols, box_rows};
    cuuint32_t es[2] = {1, 1};
    enc(m, CU_TENSOR_MAP_DATA_TYPE_BFLOAT16, 2, const_cast<void*>(base), gd, gs, bd, es, CU_TENSOR_MAP_INTERLEAVE_NONE,
        swz, CU_TENSOR_MAP_L2_PROMOTION_L2_128B, CU_TENSOR_MAP_FLOAT_OOB_FILL_NONE);
}

}

extern "C" void kernel_launch(void* const* d_in, const int* in_sizes, int n_in, void* d_out, int out_size) {
    (void)in_sizes; (void)n_in; (void)out_size;
    static EncodeFn enc = nullptr;
    if (!enc) {
        void* fn = nullptr;
        cudaDriverEntryPointQueryResult qr;
        cudaGetDriverEntryPoint("cuTensorMapEncodeTiled", &fn, cudaEnableDefault, &qr);
        enc = reinterpret_cast<EncodeFn>(fn);
        cudaFuncSetAttribute(fused_decode_kernel, cudaFuncAttributeMaxDynamicSharedMemorySize, SMEM_BYTES);
    }
    CUtensorMap tk, tv, tvp, twq, two, twg, twu, twd;
    encode2d(enc, &tk, d_in[1], 64, (uint64_t)kB * kHKV * kSK * 2, 128, 64, 256, CU_TENSOR_MAP_SWIZZLE_128B);
    encode2d(enc, &tv, d_in[2], 64, (uint64_t)kB * kHKV * kSK * 2, 128, 64, 256, CU_TENSOR_MAP_SWIZZLE_128B);
    encode2d(enc, &tvp, d_in[2], 64, (uint64_t)kB * kHKV * kSK * 2, 128, 64, 256 / NVP, CU_TENSOR_MAP_SWIZZLE_128B);
    encode2d(enc, &twq, d_in[3], kHQ * kDH, kD, kHQ * kDH * 2, 32, 256, CU_TENSOR_MAP_SWIZZLE_64B);
    encode2d(enc, &two, d_in[4], kD, kHQ * kDH, kD * 2, 64, 128, CU_TENSOR_MAP_SWIZZLE_128B);
    encode2d(enc, &twg, d_in[6], kF, kD, kF * 2, 64, 256, CU_TENSOR_MAP_SWIZZLE_128B);
    encode2d(enc, &twu, d_in[7], kF, kD, kF * 2, 64, 256, CU_TENSOR_MAP_SWIZZLE_128B);
    encode2d(enc, &twd, d_in[8], kD, kF, kD * 2, 64, DROWS, CU_TENSOR_MAP_SWIZZLE_128B);
    Params prm;
    prm.x = reinterpret_cast<const __nv_bfloat16*>(d_in[0]);
    prm.gate_w = reinterpret_cast<const __nv_bfloat16*>(d_in[9]);
    prm.out = reinterpret_cast<__nv_bfloat16*>(d_out);
    fused_decode_kernel<<<NCTA, NTHREADS, SMEM_BYTES>>>(tk, tv, tvp, twq, two, twg, twu, twd, prm);
}
```
